```python
import torch

def _softmax(x, axis=-1):
    return torch.softmax(x, dim=axis)

def _gelu(x):
    return torch.nn.functional.gelu(x, approximate='tanh')

def _silu(x):
    return torch.nn.functional.silu(x)

def _sigmoid(x):
    return torch.sigmoid(x)

def _layernorm(x, axis=-1, eps=1e-05):
    m = x.mean(dim=axis, keepdim=True)
    v = x.var(dim=axis, keepdim=True, unbiased=False)
    return (x - m) / torch.sqrt(v + eps)

def _scatter_add(tgt, idx, src, axis=0):
    return tgt.clone().index_add_(axis, idx, src)

def _segment_sum(src, seg, n):
    out = torch.zeros((n,) + src.shape[1:], dtype=src.dtype)
    return out.index_add_(0, seg, src)

def _pad(x, pw):
    flat = tuple((v for pair in reversed(pw) for v in pair))
    return torch.nn.functional.pad(x, flat)
kernel_name = 'gated_mix__memory_aug_recurrent_mem_tr__dense_activation_relu__prompt'

def setup_inputs():

    _w = lambda a: (lambda t: t.to(torch.bfloat16) if t.is_floating_point() else t)(torch.as_tensor(a))

    def _A_setup():
        B, S, Dm = (1, 2048, 448)
        H, Dh = (16, 256)
        M, seg = (8, 32)
        seg = min(seg, S)
        S = S // seg * seg
        return {'x': _w((lambda *s: torch.randn(*s, dtype=torch.bfloat16) * 0.05)(B, S, Dm)), 'mem0': _w((lambda *s: torch.randn(*s, dtype=torch.bfloat16) * 0.8)(B, M, Dm)), 'Wq': _w((lambda *s: torch.randn(*s, dtype=torch.bfloat16) * 3.2)(Dm, H, Dh) * Dm ** (-0.5)), 'Wk': _w((lambda *s: torch.randn(*s, dtype=torch.bfloat16) * 3.2)(Dm, H, Dh) * Dm ** (-0.5)), 'Wv': _w((lambda *s: torch.randn(*s, dtype=torch.bfloat16) * 0.8)(Dm, H, Dh) * Dm ** (-0.5)), 'Wo': _w((lambda *s: torch.randn(*s, dtype=torch.bfloat16) * 0.8)(H, Dh, Dm) * (H * Dh) ** (-0.5)), 'seg_len': seg}
    _A_in = _A_setup()

    def _B_setup():
        B, S, D, Dff = (1, 2048, 448, 1792)
        return {'x': _w((lambda *s: torch.randn(*s, dtype=torch.bfloat16) * 0.05)(B, S, D)), 'w1': _w((lambda *s: torch.randn(*s, dtype=torch.bfloat16) * 0.05)(D, Dff)), 'w2': _w((lambda *s: torch.randn(*s, dtype=torch.bfloat16) * 0.05)(Dff, D))}
    _B_in = _B_setup()
    return {'A_x': _A_in['x'], 'A_mem0': _A_in['mem0'], 'A_Wq': _A_in['Wq'], 'A_Wk': _A_in['Wk'], 'A_Wv': _A_in['Wv'], 'A_Wo': _A_in['Wo'], 'A_seg_len': _A_in['seg_len'], 'B_x': _B_in['x'], 'B_w1': _B_in['w1'], 'B_w2': _B_in['w2'], 'gate_w': _w((lambda *s: torch.randn(*s, dtype=torch.bfloat16) * 0.05)(448) * 16.0)}

def reference(A_x, A_mem0, A_Wq, A_Wk, A_Wv, A_Wo, A_seg_len, B_x, B_w1, B_w2, gate_w):

    def _A_ref(x, mem0, Wq, Wk, Wv, Wo, seg_len):
        B, S, Dm = x.shape
        H, Dh = (Wq.shape[1], Wq.shape[2])
        M = mem0.shape[1]
        scale = Dh ** (-0.5)
        n_seg = S // seg_len
        L = M + seg_len
        idx = torch.arange(L)
        mask = (idx[:, None] < M) | (idx[:, None] >= idx[None, :])
        mem = mem0
        outs = []
        for s in range(n_seg):
            xs = x[:, s * seg_len:(s + 1) * seg_len, :].clone()
            h = torch.concatenate([mem, xs], axis=1)
            q = torch.einsum('btd,dhe->bhte', h, Wq)
            k = torch.einsum('btd,dhe->bhte', h, Wk)
            v = torch.einsum('btd,dhe->bhte', h, Wv)
            scores = torch.einsum('bhqe,bhke->bhqk', q, k) * scale
            scores = torch.where(mask[None, None], scores, -1000000000.0)
            p = _softmax(scores, axis=-1)
            o = torch.einsum('bhqk,bhke->bhqe', p, v)
            o = torch.einsum('bhte,hed->btd', o, Wo)
            mem = o[:, :M, :].clone()
            outs.append(o[:, M:, :])
        return torch.concatenate(outs, axis=1)

    def _B_ref(x, w1, w2):
        h = torch.einsum('bsd,df->bsf', x, w1)
        zero = torch.zeros_like(h)
        h = torch.maximum(h, zero)
        return torch.einsum('bsf,fd->bsd', h, w2)
    x = A_x
    g = _sigmoid((x * gate_w).sum(-1, keepdims=True))
    a = _A_ref(x, A_mem0, A_Wq, A_Wk, A_Wv, A_Wo, A_seg_len)
    b = _B_ref(x, B_w1, B_w2)
    return g * a + (1 - g) * b
```

```cpp
#define POLITE 54
#define NWORK 132
#include <cuda.h>
#include <cuda_runtime.h>
#include <cuda_bf16.h>
#include <stdint.h>
#include <stddef.h>

typedef __nv_bfloat16 bf16;

__device__ __forceinline__ uint32_t smem_u32(const void* p) { return (uint32_t)__cvta_generic_to_shared(p); }
__device__ __forceinline__ uint32_t mapa(uint32_t a, uint32_t r) {
  uint32_t o; asm("mapa.shared::cluster.u32 %0, %1, %2;" : "=r"(o) : "r"(a), "r"(r)); return o;
}
__device__ __forceinline__ void cluster_sync_all() {
  asm volatile("barrier.cluster.arrive.aligned; barrier.cluster.wait.aligned;" ::: "memory");
}
__device__ __forceinline__ void mbar_init(uint32_t bar, uint32_t cnt) {
  asm volatile("mbarrier.init.shared::cta.b64 [%0], %1;" ::"r"(bar), "r"(cnt) : "memory");
}
__device__ __forceinline__ void mbar_arrive(uint32_t bar) {
  asm volatile("mbarrier.arrive.shared::cta.b64 _, [%0];" ::"r"(bar) : "memory");
}
__device__ __forceinline__ void mbar_arrive_tx(uint32_t bar, uint32_t bytes) {
  asm volatile("mbarrier.arrive.expect_tx.shared::cta.b64 _, [%0], %1;" ::"r"(bar), "r"(bytes) : "memory");
}
__device__ __forceinline__ void mbar_arrive_remote(uint32_t bar) {
  asm volatile("mbarrier.arrive.shared::cluster.b64 _, [%0];" ::"r"(bar) : "memory");
}
__device__ __forceinline__ void mbar_wait(uint32_t bar, uint32_t par, int& budget) {
  asm volatile("{\n.reg .pred p, q;\n"
               "W_LOOP:\n"
               "mbarrier.try_wait.parity.shared::cta.b64 p, [%1], %2;\n"
               "@p bra.uni W_DONE;\n"
               "sub.s32 %0, %0, 1;\n"
               "setp.gt.s32 q, %0, 0;\n"
               "@q bra.uni W_LOOP;\n"
               "W_DONE:\n}"
               : "+r"(budget) : "r"(bar), "r"(par) : "memory");
}
__device__ __forceinline__ void bar_sync(int id, int n) { asm volatile("bar.sync %0, %1;" ::"r"(id), "r"(n) : "memory"); }
__device__ __forceinline__ void bar_arrive(int id, int n) { asm volatile("bar.arrive %0, %1;" ::"r"(id), "r"(n) : "memory"); }

__device__ __forceinline__ void mma16816(float (&c)[4], uint32_t a0, uint32_t a1, uint32_t a2, uint32_t a3, uint32_t b0, uint32_t b1) {
  asm("mma.sync.aligned.m16n8k16.row.col.f32.bf16.bf16.f32 {%0,%1,%2,%3},{%4,%5,%6,%7},{%8,%9},{%0,%1,%2,%3};"
      : "+f"(c[0]), "+f"(c[1]), "+f"(c[2]), "+f"(c[3]) : "r"(a0), "r"(a1), "r"(a2), "r"(a3), "r"(b0), "r"(b1));
}
__device__ __forceinline__ void mma16816_z(float (&c)[4], uint32_t a0, uint32_t a1, uint32_t a2, uint32_t a3, uint32_t b0, uint32_t b1) {
  asm("mma.sync.aligned.m16n8k16.row.col.f32.bf16.bf16.f32 {%0,%1,%2,%3},{%4,%5,%6,%7},{%8,%9},{%10,%10,%10,%10};"
      : "=f"(c[0]), "=f"(c[1]), "=f"(c[2]), "=f"(c[3]) : "r"(a0), "r"(a1), "r"(a2), "r"(a3), "r"(b0), "r"(b1), "f"(0.f));
}
__device__ __forceinline__ void mma1688(float (&c)[4], uint32_t a0, uint32_t a1, uint32_t b0) {
  asm("mma.sync.aligned.m16n8k8.row.col.f32.bf16.bf16.f32 {%0,%1,%2,%3},{%4,%5},{%6},{%0,%1,%2,%3};"
      : "+f"(c[0]), "+f"(c[1]), "+f"(c[2]), "+f"(c[3]) : "r"(a0), "r"(a1), "r"(b0));
}
__device__ __forceinline__ uint32_t pack2(float lo, float hi) {
  uint32_t o; asm("cvt.rn.bf16x2.f32 %0, %1, %2;" : "=r"(o) : "f"(hi), "f"(lo)); return o;
}
__device__ __forceinline__ float bf_lo(uint32_t v) { return __uint_as_float(v << 16); }
__device__ __forceinline__ float bf_hi(uint32_t v) { return __uint_as_float(v & 0xffff0000u); }
__device__ __forceinline__ float ex2(float x) { float y; asm("ex2.approx.ftz.f32 %0, %1;" : "=f"(y) : "f"(x)); return y; }
__device__ __forceinline__ float rcp(float x) { float y; asm("rcp.approx.ftz.f32 %0, %1;" : "=f"(y) : "f"(x)); return y; }

__device__ __forceinline__ void ldsm4(uint32_t (&r)[4], uint32_t a) {
  asm volatile("ldmatrix.sync.aligned.m8n8.x4.shared.b16 {%0,%1,%2,%3}, [%4];" : "=r"(r[0]), "=r"(r[1]), "=r"(r[2]), "=r"(r[3]) : "r"(a) : "memory");
}
__device__ __forceinline__ void ldsm4t(uint32_t (&r)[4], uint32_t a) {
  asm volatile("ldmatrix.sync.aligned.m8n8.x4.trans.shared.b16 {%0,%1,%2,%3}, [%4];" : "=r"(r[0]), "=r"(r[1]), "=r"(r[2]), "=r"(r[3]) : "r"(a) : "memory");
}
__device__ __forceinline__ uint4 lds128(uint32_t a) {
  uint4 v; asm volatile("ld.shared.v4.b32 {%0,%1,%2,%3}, [%4];" : "=r"(v.x), "=r"(v.y), "=r"(v.z), "=r"(v.w) : "r"(a) : "memory"); return v;
}
__device__ __forceinline__ float4 lds128f(uint32_t a) {
  float4 v; asm volatile("ld.shared.v4.f32 {%0,%1,%2,%3}, [%4];" : "=f"(v.x), "=f"(v.y), "=f"(v.z), "=f"(v.w) : "r"(a) : "memory"); return v;
}
__device__ __forceinline__ uint2 lds64(uint32_t a) {
  uint2 v; asm volatile("ld.shared.v2.b32 {%0,%1}, [%2];" : "=r"(v.x), "=r"(v.y) : "r"(a) : "memory"); return v;
}
__device__ __forceinline__ float2 lds64f(uint32_t a) {
  float2 v; asm volatile("ld.shared.v2.f32 {%0,%1}, [%2];" : "=f"(v.x), "=f"(v.y) : "r"(a) : "memory"); return v;
}
__device__ __forceinline__ uint32_t lds32(uint32_t a) {
  uint32_t v; asm volatile("ld.shared.b32 %0, [%1];" : "=r"(v) : "r"(a) : "memory"); return v;
}
__device__ __forceinline__ void sts32(uint32_t a, uint32_t v) { asm volatile("st.shared.b32 [%0], %1;" ::"r"(a), "r"(v) : "memory"); }
__device__ __forceinline__ void sts64(uint32_t a, uint32_t x, uint32_t y) { asm volatile("st.shared.v2.b32 [%0], {%1,%2};" ::"r"(a), "r"(x), "r"(y) : "memory"); }
__device__ __forceinline__ void sts128(uint32_t a, uint32_t x, uint32_t y, uint32_t z, uint32_t w) {
  asm volatile("st.shared.v4.b32 [%0], {%1,%2,%3,%4};" ::"r"(a), "r"(x), "r"(y), "r"(z), "r"(w) : "memory");
}
__device__ __forceinline__ void sts128f(uint32_t a, const float (&c)[4]) {
  asm volatile("st.shared.v4.f32 [%0], {%1,%2,%3,%4};" ::"r"(a), "f"(c[0]), "f"(c[1]), "f"(c[2]), "f"(c[3]) : "memory");
}
__device__ __forceinline__ void stasync32(uint32_t a, uint32_t v, uint32_t bar) {
  asm volatile("st.async.shared::cluster.mbarrier::complete_tx::bytes.b32 [%0], %1, [%2];" ::"r"(a), "r"(v), "r"(bar) : "memory");
}
__device__ __forceinline__ void stasync64(uint32_t a, uint32_t x, uint32_t y, uint32_t bar) {
  asm volatile("st.async.shared::cluster.mbarrier::complete_tx::bytes.v2.b32 [%0], {%1,%2}, [%3];" ::"r"(a), "r"(x), "r"(y), "r"(bar) : "memory");
}
__device__ __forceinline__ void tma2d(uint32_t dst, const CUtensorMap* tm, int c0, int c1, uint32_t bar) {
  asm volatile("cp.async.bulk.tensor.2d.shared::cluster.global.mbarrier::complete_tx::bytes [%0], [%1, {%3, %4}], [%2];"
               ::"r"(dst), "l"(tm), "r"(bar), "r"(c0), "r"(c1) : "memory");
}
__device__ __forceinline__ void tma2d_mc(uint32_t dst, const CUtensorMap* tm, int c0, int c1, uint32_t bar, uint16_t mask) {
  asm volatile("cp.async.bulk.tensor.2d.shared::cluster.global.mbarrier::complete_tx::bytes.multicast::cluster [%0], [%1, {%3, %4}], [%2], %5;"
               ::"r"(dst), "l"(tm), "r"(bar), "r"(c0), "r"(c1), "h"(mask) : "memory");
}
__device__ __forceinline__ void fence_proxy_async() { asm volatile("fence.proxy.async;" ::: "memory"); }
__device__ __forceinline__ void fence_proxy_async_smem() { asm volatile("fence.proxy.async.shared::cta;" ::: "memory"); }
__device__ __forceinline__ uint32_t ld_acquire(const uint32_t* p) {
  uint32_t v; asm volatile("ld.acquire.gpu.global.u32 %0, [%1];" : "=r"(v) : "l"(p) : "memory"); return v;
}
__device__ __forceinline__ uint32_t ld_relaxed(const uint32_t* p) {
  uint32_t v; asm volatile("ld.relaxed.gpu.global.u32 %0, [%1];" : "=r"(v) : "l"(p) : "memory"); return v;
}
__device__ __forceinline__ void red_release(uint32_t* p, uint32_t v) {
  asm volatile("red.release.gpu.global.add.u32 [%0], %1;" ::"l"(p), "r"(v) : "memory");
}
__device__ __forceinline__ uint32_t clk() { uint32_t c; asm volatile("mov.u32 %0, %%clock;" : "=r"(c)::"memory"); return c; }
template <int N> __device__ __forceinline__ void reg_inc() { asm volatile("setmaxnreg.inc.sync.aligned.u32 %0;" ::"n"(N)); }
template <int N> __device__ __forceinline__ void reg_dec() { asm volatile("setmaxnreg.dec.sync.aligned.u32 %0;" ::"n"(N)); }
template <int TA, int TB>
__device__ __forceinline__ void wgmma_n32(float (&d)[16], uint64_t da, uint64_t db, uint32_t acc) {
  asm volatile("{.reg .pred p; setp.ne.u32 p, %18, 0;\n"
      "wgmma.mma_async.sync.aligned.m64n32k16.f32.bf16.bf16 {%0,%1,%2,%3,%4,%5,%6,%7,%8,%9,%10,%11,%12,%13,%14,%15}, %16, %17, p, 1, 1, %19, %20;}"
      : "+f"(d[0]), "+f"(d[1]), "+f"(d[2]), "+f"(d[3]), "+f"(d[4]), "+f"(d[5]), "+f"(d[6]), "+f"(d[7]), "+f"(d[8]), "+f"(d[9]), "+f"(d[10]), "+f"(d[11]), "+f"(d[12]), "+f"(d[13]), "+f"(d[14]), "+f"(d[15])
      : "l"(da), "l"(db), "r"(acc), "n"(TA), "n"(TB));
}
template <int TA, int TB>
__device__ __forceinline__ void wgmma_n128(float (&d)[64], uint64_t da, uint64_t db, uint32_t acc) {
  asm volatile("{.reg .pred p; setp.ne.u32 p, %66, 0;\n"
      "wgmma.mma_async.sync.aligned.m64n128k16.f32.bf16.bf16 {%0,%1,%2,%3,%4,%5,%6,%7,%8,%9,%10,%11,%12,%13,%14,%15,%16,%17,%18,%19,%20,%21,%22,%23,%24,%25,%26,%27,%28,%29,%30,%31,%32,%33,%34,%35,%36,%37,%38,%39,%40,%41,%42,%43,%44,%45,%46,%47,%48,%49,%50,%51,%52,%53,%54,%55,%56,%57,%58,%59,%60,%61,%62,%63}, %64, %65, p, 1, 1, %67, %68;}"
      : "+f"(d[0]), "+f"(d[1]), "+f"(d[2]), "+f"(d[3]), "+f"(d[4]), "+f"(d[5]), "+f"(d[6]), "+f"(d[7]), "+f"(d[8]), "+f"(d[9]), "+f"(d[10]), "+f"(d[11]), "+f"(d[12]), "+f"(d[13]), "+f"(d[14]), "+f"(d[15]), "+f"(d[16]), "+f"(d[17]), "+f"(d[18]), "+f"(d[19]), "+f"(d[20]), "+f"(d[21]), "+f"(d[22]), "+f"(d[23]), "+f"(d[24]), "+f"(d[25]), "+f"(d[26]), "+f"(d[27]), "+f"(d[28]), "+f"(d[29]), "+f"(d[30]), "+f"(d[31]), "+f"(d[32]), "+f"(d[33]), "+f"(d[34]), "+f"(d[35]), "+f"(d[36]), "+f"(d[37]), "+f"(d[38]), "+f"(d[39]), "+f"(d[40]), "+f"(d[41]), "+f"(d[42]), "+f"(d[43]), "+f"(d[44]), "+f"(d[45]), "+f"(d[46]), "+f"(d[47]), "+f"(d[48]), "+f"(d[49]), "+f"(d[50]), "+f"(d[51]), "+f"(d[52]), "+f"(d[53]), "+f"(d[54]), "+f"(d[55]), "+f"(d[56]), "+f"(d[57]), "+f"(d[58]), "+f"(d[59]), "+f"(d[60]), "+f"(d[61]), "+f"(d[62]), "+f"(d[63])
      : "l"(da), "l"(db), "r"(acc), "n"(TA), "n"(TB));
}
template <int TA, int TB>
__device__ __forceinline__ void wgmma_n144(float (&d)[72], uint64_t da, uint64_t db, uint32_t acc) {
  asm volatile("{.reg .pred p; setp.ne.u32 p, %74, 0;\n"
      "wgmma.mma_async.sync.aligned.m64n144k16.f32.bf16.bf16 {%0,%1,%2,%3,%4,%5,%6,%7,%8,%9,%10,%11,%12,%13,%14,%15,%16,%17,%18,%19,%20,%21,%22,%23,%24,%25,%26,%27,%28,%29,%30,%31,%32,%33,%34,%35,%36,%37,%38,%39,%40,%41,%42,%43,%44,%45,%46,%47,%48,%49,%50,%51,%52,%53,%54,%55,%56,%57,%58,%59,%60,%61,%62,%63,%64,%65,%66,%67,%68,%69,%70,%71}, %72, %73, p, 1, 1, %75, %76;}"
      : "+f"(d[0]), "+f"(d[1]), "+f"(d[2]), "+f"(d[3]), "+f"(d[4]), "+f"(d[5]), "+f"(d[6]), "+f"(d[7]), "+f"(d[8]), "+f"(d[9]), "+f"(d[10]), "+f"(d[11]), "+f"(d[12]), "+f"(d[13]), "+f"(d[14]), "+f"(d[15]), "+f"(d[16]), "+f"(d[17]), "+f"(d[18]), "+f"(d[19]), "+f"(d[20]), "+f"(d[21]), "+f"(d[22]), "+f"(d[23]), "+f"(d[24]), "+f"(d[25]), "+f"(d[26]), "+f"(d[27]), "+f"(d[28]), "+f"(d[29]), "+f"(d[30]), "+f"(d[31]), "+f"(d[32]), "+f"(d[33]), "+f"(d[34]), "+f"(d[35]), "+f"(d[36]), "+f"(d[37]), "+f"(d[38]), "+f"(d[39]), "+f"(d[40]), "+f"(d[41]), "+f"(d[42]), "+f"(d[43]), "+f"(d[44]), "+f"(d[45]), "+f"(d[46]), "+f"(d[47]), "+f"(d[48]), "+f"(d[49]), "+f"(d[50]), "+f"(d[51]), "+f"(d[52]), "+f"(d[53]), "+f"(d[54]), "+f"(d[55]), "+f"(d[56]), "+f"(d[57]), "+f"(d[58]), "+f"(d[59]), "+f"(d[60]), "+f"(d[61]), "+f"(d[62]), "+f"(d[63]), "+f"(d[64]), "+f"(d[65]), "+f"(d[66]), "+f"(d[67]), "+f"(d[68]), "+f"(d[69]), "+f"(d[70]), "+f"(d[71])
      : "l"(da), "l"(db), "r"(acc), "n"(TA), "n"(TB));
}
template <int TA, int TB>
__device__ __forceinline__ void wgmma_n152(float (&d)[76], uint64_t da, uint64_t db, uint32_t acc) {
  asm volatile("{.reg .pred p; setp.ne.u32 p, %78, 0;\n"
      "wgmma.mma_async.sync.aligned.m64n152k16.f32.bf16.bf16 {%0,%1,%2,%3,%4,%5,%6,%7,%8,%9,%10,%11,%12,%13,%14,%15,%16,%17,%18,%19,%20,%21,%22,%23,%24,%25,%26,%27,%28,%29,%30,%31,%32,%33,%34,%35,%36,%37,%38,%39,%40,%41,%42,%43,%44,%45,%46,%47,%48,%49,%50,%51,%52,%53,%54,%55,%56,%57,%58,%59,%60,%61,%62,%63,%64,%65,%66,%67,%68,%69,%70,%71,%72,%73,%74,%75}, %76, %77, p, 1, 1, %79, %80;}"
      : "+f"(d[0]), "+f"(d[1]), "+f"(d[2]), "+f"(d[3]), "+f"(d[4]), "+f"(d[5]), "+f"(d[6]), "+f"(d[7]), "+f"(d[8]), "+f"(d[9]), "+f"(d[10]), "+f"(d[11]), "+f"(d[12]), "+f"(d[13]), "+f"(d[14]), "+f"(d[15]), "+f"(d[16]), "+f"(d[17]), "+f"(d[18]), "+f"(d[19]), "+f"(d[20]), "+f"(d[21]), "+f"(d[22]), "+f"(d[23]), "+f"(d[24]), "+f"(d[25]), "+f"(d[26]), "+f"(d[27]), "+f"(d[28]), "+f"(d[29]), "+f"(d[30]), "+f"(d[31]), "+f"(d[32]), "+f"(d[33]), "+f"(d[34]), "+f"(d[35]), "+f"(d[36]), "+f"(d[37]), "+f"(d[38]), "+f"(d[39]), "+f"(d[40]), "+f"(d[41]), "+f"(d[42]), "+f"(d[43]), "+f"(d[44]), "+f"(d[45]), "+f"(d[46]), "+f"(d[47]), "+f"(d[48]), "+f"(d[49]), "+f"(d[50]), "+f"(d[51]), "+f"(d[52]), "+f"(d[53]), "+f"(d[54]), "+f"(d[55]), "+f"(d[56]), "+f"(d[57]), "+f"(d[58]), "+f"(d[59]), "+f"(d[60]), "+f"(d[61]), "+f"(d[62]), "+f"(d[63]), "+f"(d[64]), "+f"(d[65]), "+f"(d[66]), "+f"(d[67]), "+f"(d[68]), "+f"(d[69]), "+f"(d[70]), "+f"(d[71]), "+f"(d[72]), "+f"(d[73]), "+f"(d[74]), "+f"(d[75])
      : "l"(da), "l"(db), "r"(acc), "n"(TA), "n"(TB));
}
template <int TA, int TB>
__device__ __forceinline__ void wgmma_n192(float (&d)[96], uint64_t da, uint64_t db, uint32_t acc) {
  asm volatile("{.reg .pred p; setp.ne.u32 p, %98, 0;\n"
      "wgmma.mma_async.sync.aligned.m64n192k16.f32.bf16.bf16 {%0,%1,%2,%3,%4,%5,%6,%7,%8,%9,%10,%11,%12,%13,%14,%15,%16,%17,%18,%19,%20,%21,%22,%23,%24,%25,%26,%27,%28,%29,%30,%31,%32,%33,%34,%35,%36,%37,%38,%39,%40,%41,%42,%43,%44,%45,%46,%47,%48,%49,%50,%51,%52,%53,%54,%55,%56,%57,%58,%59,%60,%61,%62,%63,%64,%65,%66,%67,%68,%69,%70,%71,%72,%73,%74,%75,%76,%77,%78,%79,%80,%81,%82,%83,%84,%85,%86,%87,%88,%89,%90,%91,%92,%93,%94,%95}, %96, %97, p, 1, 1, %99, %100;}"
      : "+f"(d[0]), "+f"(d[1]), "+f"(d[2]), "+f"(d[3]), "+f"(d[4]), "+f"(d[5]), "+f"(d[6]), "+f"(d[7]), "+f"(d[8]), "+f"(d[9]), "+f"(d[10]), "+f"(d[11]), "+f"(d[12]), "+f"(d[13]), "+f"(d[14]), "+f"(d[15]), "+f"(d[16]), "+f"(d[17]), "+f"(d[18]), "+f"(d[19]), "+f"(d[20]), "+f"(d[21]), "+f"(d[22]), "+f"(d[23]), "+f"(d[24]), "+f"(d[25]), "+f"(d[26]), "+f"(d[27]), "+f"(d[28]), "+f"(d[29]), "+f"(d[30]), "+f"(d[31]), "+f"(d[32]), "+f"(d[33]), "+f"(d[34]), "+f"(d[35]), "+f"(d[36]), "+f"(d[37]), "+f"(d[38]), "+f"(d[39]), "+f"(d[40]), "+f"(d[41]), "+f"(d[42]), "+f"(d[43]), "+f"(d[44]), "+f"(d[45]), "+f"(d[46]), "+f"(d[47]), "+f"(d[48]), "+f"(d[49]), "+f"(d[50]), "+f"(d[51]), "+f"(d[52]), "+f"(d[53]), "+f"(d[54]), "+f"(d[55]), "+f"(d[56]), "+f"(d[57]), "+f"(d[58]), "+f"(d[59]), "+f"(d[60]), "+f"(d[61]), "+f"(d[62]), "+f"(d[63]), "+f"(d[64]), "+f"(d[65]), "+f"(d[66]), "+f"(d[67]), "+f"(d[68]), "+f"(d[69]), "+f"(d[70]), "+f"(d[71]), "+f"(d[72]), "+f"(d[73]), "+f"(d[74]), "+f"(d[75]), "+f"(d[76]), "+f"(d[77]), "+f"(d[78]), "+f"(d[79]), "+f"(d[80]), "+f"(d[81]), "+f"(d[82]), "+f"(d[83]), "+f"(d[84]), "+f"(d[85]), "+f"(d[86]), "+f"(d[87]), "+f"(d[88]), "+f"(d[89]), "+f"(d[90]), "+f"(d[91]), "+f"(d[92]), "+f"(d[93]), "+f"(d[94]), "+f"(d[95])
      : "l"(da), "l"(db), "r"(acc), "n"(TA), "n"(TB));
}
template <int TA, int TB>
__device__ __forceinline__ void wgmma_n256(float (&d)[128], uint64_t da, uint64_t db, uint32_t acc) {
  asm volatile("{.reg .pred p; setp.ne.u32 p, %130, 0;\n"
      "wgmma.mma_async.sync.aligned.m64n256k16.f32.bf16.bf16 {%0,%1,%2,%3,%4,%5,%6,%7,%8,%9,%10,%11,%12,%13,%14,%15,%16,%17,%18,%19,%20,%21,%22,%23,%24,%25,%26,%27,%28,%29,%30,%31,%32,%33,%34,%35,%36,%37,%38,%39,%40,%41,%42,%43,%44,%45,%46,%47,%48,%49,%50,%51,%52,%53,%54,%55,%56,%57,%58,%59,%60,%61,%62,%63,%64,%65,%66,%67,%68,%69,%70,%71,%72,%73,%74,%75,%76,%77,%78,%79,%80,%81,%82,%83,%84,%85,%86,%87,%88,%89,%90,%91,%92,%93,%94,%95,%96,%97,%98,%99,%100,%101,%102,%103,%104,%105,%106,%107,%108,%109,%110,%111,%112,%113,%114,%115,%116,%117,%118,%119,%120,%121,%122,%123,%124,%125,%126,%127}, %128, %129, p, 1, 1, %131, %132;}"
      : "+f"(d[0]), "+f"(d[1]), "+f"(d[2]), "+f"(d[3]), "+f"(d[4]), "+f"(d[5]), "+f"(d[6]), "+f"(d[7]), "+f"(d[8]), "+f"(d[9]), "+f"(d[10]), "+f"(d[11]), "+f"(d[12]), "+f"(d[13]), "+f"(d[14]), "+f"(d[15]), "+f"(d[16]), "+f"(d[17]), "+f"(d[18]), "+f"(d[19]), "+f"(d[20]), "+f"(d[21]), "+f"(d[22]), "+f"(d[23]), "+f"(d[24]), "+f"(d[25]), "+f"(d[26]), "+f"(d[27]), "+f"(d[28]), "+f"(d[29]), "+f"(d[30]), "+f"(d[31]), "+f"(d[32]), "+f"(d[33]), "+f"(d[34]), "+f"(d[35]), "+f"(d[36]), "+f"(d[37]), "+f"(d[38]), "+f"(d[39]), "+f"(d[40]), "+f"(d[41]), "+f"(d[42]), "+f"(d[43]), "+f"(d[44]), "+f"(d[45]), "+f"(d[46]), "+f"(d[47]), "+f"(d[48]), "+f"(d[49]), "+f"(d[50]), "+f"(d[51]), "+f"(d[52]), "+f"(d[53]), "+f"(d[54]), "+f"(d[55]), "+f"(d[56]), "+f"(d[57]), "+f"(d[58]), "+f"(d[59]), "+f"(d[60]), "+f"(d[61]), "+f"(d[62]), "+f"(d[63]), "+f"(d[64]), "+f"(d[65]), "+f"(d[66]), "+f"(d[67]), "+f"(d[68]), "+f"(d[69]), "+f"(d[70]), "+f"(d[71]), "+f"(d[72]), "+f"(d[73]), "+f"(d[74]), "+f"(d[75]), "+f"(d[76]), "+f"(d[77]), "+f"(d[78]), "+f"(d[79]), "+f"(d[80]), "+f"(d[81]), "+f"(d[82]), "+f"(d[83]), "+f"(d[84]), "+f"(d[85]), "+f"(d[86]), "+f"(d[87]), "+f"(d[88]), "+f"(d[89]), "+f"(d[90]), "+f"(d[91]), "+f"(d[92]), "+f"(d[93]), "+f"(d[94]), "+f"(d[95]), "+f"(d[96]), "+f"(d[97]), "+f"(d[98]), "+f"(d[99]), "+f"(d[100]), "+f"(d[101]), "+f"(d[102]), "+f"(d[103]), "+f"(d[104]), "+f"(d[105]), "+f"(d[106]), "+f"(d[107]), "+f"(d[108]), "+f"(d[109]), "+f"(d[110]), "+f"(d[111]), "+f"(d[112]), "+f"(d[113]), "+f"(d[114]), "+f"(d[115]), "+f"(d[116]), "+f"(d[117]), "+f"(d[118]), "+f"(d[119]), "+f"(d[120]), "+f"(d[121]), "+f"(d[122]), "+f"(d[123]), "+f"(d[124]), "+f"(d[125]), "+f"(d[126]), "+f"(d[127])
      : "l"(da), "l"(db), "r"(acc), "n"(TA), "n"(TB));
}

template <int TB>
__device__ __forceinline__ void wgmma_rs_n64(float (&d)[32], const uint32_t* a, uint64_t db) {
  asm volatile("wgmma.mma_async.sync.aligned.m64n64k16.f32.bf16.bf16 {%0,%1,%2,%3,%4,%5,%6,%7,%8,%9,%10,%11,%12,%13,%14,%15,%16,%17,%18,%19,%20,%21,%22,%23,%24,%25,%26,%27,%28,%29,%30,%31}, {%32,%33,%34,%35}, %36, 1, 1, 1, %37;"
      : "+f"(d[0]), "+f"(d[1]), "+f"(d[2]), "+f"(d[3]), "+f"(d[4]), "+f"(d[5]), "+f"(d[6]), "+f"(d[7]), "+f"(d[8]), "+f"(d[9]), "+f"(d[10]), "+f"(d[11]), "+f"(d[12]), "+f"(d[13]), "+f"(d[14]), "+f"(d[15]), "+f"(d[16]), "+f"(d[17]), "+f"(d[18]), "+f"(d[19]), "+f"(d[20]), "+f"(d[21]), "+f"(d[22]), "+f"(d[23]), "+f"(d[24]), "+f"(d[25]), "+f"(d[26]), "+f"(d[27]), "+f"(d[28]), "+f"(d[29]), "+f"(d[30]), "+f"(d[31])
      : "r"(a[0]), "r"(a[1]), "r"(a[2]), "r"(a[3]), "l"(db), "n"(TB));
}
template <int TB>
__device__ __forceinline__ void wgmma_rs_n128(float (&d)[64], const uint32_t* a, uint64_t db) {
  asm volatile("wgmma.mma_async.sync.aligned.m64n128k16.f32.bf16.bf16 {%0,%1,%2,%3,%4,%5,%6,%7,%8,%9,%10,%11,%12,%13,%14,%15,%16,%17,%18,%19,%20,%21,%22,%23,%24,%25,%26,%27,%28,%29,%30,%31,%32,%33,%34,%35,%36,%37,%38,%39,%40,%41,%42,%43,%44,%45,%46,%47,%48,%49,%50,%51,%52,%53,%54,%55,%56,%57,%58,%59,%60,%61,%62,%63}, {%64,%65,%66,%67}, %68, 1, 1, 1, %69;"
      : "+f"(d[0]), "+f"(d[1]), "+f"(d[2]), "+f"(d[3]), "+f"(d[4]), "+f"(d[5]), "+f"(d[6]), "+f"(d[7]), "+f"(d[8]), "+f"(d[9]), "+f"(d[10]), "+f"(d[11]), "+f"(d[12]), "+f"(d[13]), "+f"(d[14]), "+f"(d[15]), "+f"(d[16]), "+f"(d[17]), "+f"(d[18]), "+f"(d[19]), "+f"(d[20]), "+f"(d[21]), "+f"(d[22]), "+f"(d[23]), "+f"(d[24]), "+f"(d[25]), "+f"(d[26]), "+f"(d[27]), "+f"(d[28]), "+f"(d[29]), "+f"(d[30]), "+f"(d[31]), "+f"(d[32]), "+f"(d[33]), "+f"(d[34]), "+f"(d[35]), "+f"(d[36]), "+f"(d[37]), "+f"(d[38]), "+f"(d[39]), "+f"(d[40]), "+f"(d[41]), "+f"(d[42]), "+f"(d[43]), "+f"(d[44]), "+f"(d[45]), "+f"(d[46]), "+f"(d[47]), "+f"(d[48]), "+f"(d[49]), "+f"(d[50]), "+f"(d[51]), "+f"(d[52]), "+f"(d[53]), "+f"(d[54]), "+f"(d[55]), "+f"(d[56]), "+f"(d[57]), "+f"(d[58]), "+f"(d[59]), "+f"(d[60]), "+f"(d[61]), "+f"(d[62]), "+f"(d[63])
      : "r"(a[0]), "r"(a[1]), "r"(a[2]), "r"(a[3]), "l"(db), "n"(TB));
}

constexpr int D = 448, NH = 16, NSEG = 64, SEG = 32, MT = 8, CL = 7, NCH = 8;
constexpr int NTOK = 2048, DFF = 1792, UROWS = 768;
constexpr int UMEM = 512, UFFN = 640;
constexpr int NHELP = 6;

__device__ bf16 g_At[NH * D * D];
__device__ bf16 g_VOt[NH * D * D];
__device__ bf16 g_U[NSEG * UROWS * D];
__device__ bf16 g_P[NTOK * UROWS];
__device__ bf16 g_mem[NSEG * MT * D];
__device__ float g_gate[NTOK];
__device__ uint32_t g_ring[30 * 2048];
__device__ uint32_t g_side[256];
struct Flags { uint32_t mem[NSEG], um[NSEG], ux[32 * 8], p[NSEG], f[16], queue, pad0[15], side[2], pad[30]; };
__device__ Flags g_fl;
constexpr uint32_t T_MEM = CL, T_UM = NCH * CL, T_UX = NHELP, T_P = 32, T_F = 8;

struct PrepMaps { CUtensorMap wq152, wq144, wv152, wv144, wo256, wk3, a152, a144, v152, v144; };
struct Maps { CUtensorMap x32, x64, u16, u32, u64, m8, a64, v64; };
struct WorkMaps { CUtensorMap u32, m3, o32, x128, u128, a256, a192, w1a, w1b, w2b, w2c, w2d, p3; };

__device__ __forceinline__ void tma3d(uint32_t dst, const CUtensorMap* tm, int c0, int c1, int c2, uint32_t bar) {
  asm volatile("cp.async.bulk.tensor.3d.shared::cluster.global.mbarrier::complete_tx::bytes [%0], [%1, {%3, %4, %5}], [%2];"
               ::"r"(dst), "l"(tm), "r"(bar), "r"(c0), "r"(c1), "r"(c2) : "memory");
}
__device__ __forceinline__ void tma2d_store(const CUtensorMap* tm, int c0, int c1, uint32_t src) {
  asm volatile("cp.async.bulk.tensor.2d.global.shared::cta.bulk_group [%0, {%1, %2}], [%3];" ::"l"(tm), "r"(c0), "r"(c1), "r"(src) : "memory");
}
__device__ __forceinline__ void bulk_commit() { asm volatile("cp.async.bulk.commit_group;" ::: "memory"); }
__device__ __forceinline__ void bulk_wait0() { asm volatile("cp.async.bulk.wait_group 0;" ::: "memory"); }
__device__ __forceinline__ void bulk_wait_read0() { asm volatile("cp.async.bulk.wait_group.read 0;" ::: "memory"); }
__device__ __forceinline__ void red_relaxed(uint32_t* p, uint32_t v) {
  asm volatile("red.relaxed.gpu.global.add.u32 [%0], %1;" ::"l"(p), "r"(v) : "memory");
}
__device__ __forceinline__ void stsm4(uint32_t a, uint32_t r0, uint32_t r1, uint32_t r2, uint32_t r3) {
  asm volatile("stmatrix.sync.aligned.m8n8.x4.shared.b16 [%0], {%1,%2,%3,%4};" ::"r"(a), "r"(r0), "r"(r1), "r"(r2), "r"(r3) : "memory");
}
__device__ __forceinline__ void stsm4t(uint32_t a, uint32_t r0, uint32_t r1, uint32_t r2, uint32_t r3) {
  asm volatile("stmatrix.sync.aligned.m8n8.x4.trans.shared.b16 [%0], {%1,%2,%3,%4};" ::"r"(a), "r"(r0), "r"(r1), "r"(r2), "r"(r3) : "memory");
}
__device__ __forceinline__ void wg_fence() { asm volatile("wgmma.fence.sync.aligned;" ::: "memory"); }
__device__ __forceinline__ void wg_commit() { asm volatile("wgmma.commit_group.sync.aligned;" ::: "memory"); }
template <int N> __device__ __forceinline__ void wg_wait() { asm volatile("wgmma.wait_group.sync.aligned %0;" ::"n"(N) : "memory"); }
template <int N> __device__ __forceinline__ void acc_fence(float (&d)[N]) {
#pragma unroll
  for (int i = 0; i < N; i++) asm volatile("" : "+f"(d[i])::"memory");
}
__device__ __forceinline__ uint64_t wdesc(uint32_t a) {
  return (uint64_t)((a & 0x3FFFF) >> 4) | ((uint64_t)512 << 16) | ((uint64_t)64 << 32) | ((uint64_t)1 << 62);
}
__device__ __forceinline__ void pdl_wait() { asm volatile("griddepcontrol.wait;" ::: "memory"); }
__device__ __forceinline__ void pdl_launch() { asm volatile("griddepcontrol.launch_dependents;" ::: "memory"); }
__device__ __forceinline__ void flag_wait(const uint32_t* p, uint32_t target, int& budget) {
  while (ld_acquire(p) < target) { if (--budget < 0) break; __nanosleep(64); }
}
__device__ __forceinline__ bool elect() {
  uint32_t o;
  asm volatile("{.reg .pred p; elect.sync _|p, 0xffffffff; selp.u32 %0, 1, 0, p;}" : "=r"(o));
  return o;
}
__device__ __forceinline__ char* ring_page(int L, uint32_t side) {
  const uint64_t a = (((uint64_t)g_ring + 8191) & ~(uint64_t)8191) + (uint64_t)L * 8192;
  return (char*)(a + (((__popc((uint32_t)a & 0xB2000u) ^ side) & 1) << 12));
}
__device__ __forceinline__ uint32_t probe_side(int j) {
  uint32_t best[2] = {~0u, ~0u}, v = 0;
  for (int i = 0; i < 12; i++) {
    const uint32_t* p = (const uint32_t*)ring_page(28, i & 1) + (j & 127) * 8 + v;
    const uint32_t t0 = clk();
    asm volatile("atom.relaxed.gpu.global.and.b32 %0, [%1], 0;" : "=r"(v) : "l"(p) : "memory");
    v = v > 1 ? 1 : 0;
    const uint32_t t = clk() + v - t0;
    if (i & 1) best[1] = min(best[1], t); else best[0] = min(best[0], t);
    v = 0;
  }
  return best[1] < best[0];
}

__device__ __forceinline__ uint32_t smid() { uint32_t v; asm("mov.u32 %0, %%smid;" : "=r"(v)); return v & 255; }
__device__ __forceinline__ void prefetch_map(const CUtensorMap* m) { asm volatile("prefetch.tensormap [%0];" ::"l"(m) : "memory"); }
#define PIN(x) x = __shfl_sync(0xffffffffu, x, lane)
namespace pr {
constexpr int NCTA = 96;
constexpr int A = 0;
constexpr int B = A + 98304;
constexpr int ST = B + 77824;
constexpr int BAR = ST + 38912;
constexpr int SIZE = BAR + 96;
}

template <bool V, int N>
__device__ __forceinline__ void prep_consumer(uint32_t sb, int wg, int h, int n0, const PrepMaps* tm) {
  const int lane = threadIdx.x & 31, wq = (threadIdx.x >> 5) & 3, l7 = lane & 7, li = lane >> 3;
  const bool lead = (threadIdx.x & 127) == 0;
  int budget = 1 << 16;
  const float sc = V ? 1.f : 0.0625f * 1.4426950408889634f;
  const uint32_t st = sb + pr::ST + wg * 19456, so = st + (16 * wq + l7 + 8 * (li & 1)) * (2 * N) + (li >> 1) * 16;
  mbar_wait(sb + pr::BAR + 88, 0, budget);
#pragma unroll 1
  for (int blk = wg; blk < 7; blk += 2) {
    float d[N / 2];
#pragma unroll
    for (int i = 0; i < N / 2; i++) d[i] = 0.f;
    const int sl = blk % 3;
    mbar_wait(sb + pr::BAR + blk * 8, 0, budget);
    const uint64_t da = wdesc(sb + pr::A + sl * 32768), db = wdesc(sb + pr::B);
    wg_fence();
#pragma unroll
    for (int k = 0; k < 16; k++) {
      if constexpr (N == 152) wgmma_n152<V, 0>(d, da + (k >> 2) * 512 + (k & 3) * (V ? 128 : 2), db + (k >> 2) * N * 8 + (k & 3) * 2, 1);
      else wgmma_n144<V, 0>(d, da + (k >> 2) * 512 + (k & 3) * (V ? 128 : 2), db + (k >> 2) * N * 8 + (k & 3) * 2, 1);
    }
    wg_commit();
    wg_wait<0>();
    acc_fence(d);
    if (lead) { if (blk < 4) mbar_arrive(sb + pr::BAR + 56 + blk * 8); bulk_wait_read0(); }
    bar_sync(1 + wg, 128);
#pragma unroll
    for (int i = 0; i + 1 < N / 8; i += 2)
      stsm4(so + i * 16, pack2(d[4 * i] * sc, d[4 * i + 1] * sc), pack2(d[4 * i + 2] * sc, d[4 * i + 3] * sc),
            pack2(d[4 * i + 4] * sc, d[4 * i + 5] * sc), pack2(d[4 * i + 6] * sc, d[4 * i + 7] * sc));
    if (N / 8 & 1)
      asm volatile("stmatrix.sync.aligned.m8n8.x2.shared.b16 [%0], {%1,%2};" ::"r"(so + (N / 8 - 1) * 16),
                   "r"(pack2(d[N / 2 - 4] * sc, d[N / 2 - 3] * sc)), "r"(pack2(d[N / 2 - 2] * sc, d[N / 2 - 1] * sc)) : "memory");
    fence_proxy_async_smem();
    bar_sync(1 + wg, 128);
    if (lead) {
      tma2d_store(V ? (N == 152 ? &tm->v152 : &tm->v144) : (N == 152 ? &tm->a152 : &tm->a144), n0, h * D + 64 * blk, st);
      bulk_commit();
    }
    __syncwarp();
  }
  if (lead) { bulk_wait0(); }
  __syncwarp();
}

__device__ __forceinline__ void record_side(int b) {
  if (b == 0) g_fl.side[0] = g_fl.side[1] = 0;
  g_side[smid()] = probe_side(b);
  __threadfence();
  pdl_launch();
}

__global__ void __launch_bounds__(384, 1) k_prep(const bf16* __restrict__ x, const bf16* __restrict__ gw, const __grid_constant__ PrepMaps tm) {
  extern __shared__ __align__(1024) uint8_t smem[];
  const uint32_t sb = smem_u32(smem);
  const int b = blockIdx.x, w = __reduce_max_sync(0xffffffffu, threadIdx.x >> 5), lane = threadIdx.x & 31;
  const int mi = b / 3, q = b - 3 * mi, h = mi & 15, V = mi >> 4, n0 = 152 * q;
  if (threadIdx.x == 0) {
    for (int i = 0; i < 12; i++) mbar_init(sb + pr::BAR + i * 8, 1);
    asm volatile("fence.mbarrier_init.release.cluster;" ::: "memory");
  }
  __syncthreads();
  if (w < 8) {
    reg_inc<200>();
    if (b < pr::NCTA) {
      if (V) { if (q < 2) prep_consumer<true, 152>(sb, w >> 2, h, n0, &tm); else prep_consumer<true, 144>(sb, w >> 2, h, n0, &tm); }
      else { if (q < 2) prep_consumer<false, 152>(sb, w >> 2, h, n0, &tm); else prep_consumer<false, 144>(sb, w >> 2, h, n0, &tm); }
    }
  } else {
    reg_dec<56>();
    if (w == 8) {
      int budget = 1 << 16;
      if (b < pr::NCTA) {
        if (elect()) {
          mbar_arrive_tx(sb + pr::BAR + 88, q < 2 ? 152 * 512 : 144 * 512);
          tma3d(sb + pr::B, V ? (q < 2 ? &tm.wv152 : &tm.wv144) : (q < 2 ? &tm.wq152 : &tm.wq144), 0, n0, h * 4, sb + pr::BAR + 88);
        }
        for (int i = 0; i < 7; i++) {
          if (i >= 3) mbar_wait(sb + pr::BAR + 56 + (i - 3) * 8, 0, budget);
          if (elect()) {
            const uint32_t bar = sb + pr::BAR + i * 8, dst = sb + pr::A + (i % 3) * 32768;
            mbar_arrive_tx(bar, 32768);
            if (V) tma2d(dst, &tm.wo256, 64 * i, h * 256, bar); else tma3d(dst, &tm.wk3, 0, 64 * i, h * 4, bar);
          }
        }
      }
    } else if (w == 11) {
      if (lane == 0) record_side(b);
    } else if (b < 128) {
      const int t = threadIdx.x - 288;
      for (int i = t; i < 464; i += 64) g_ring[b * 464 + i] = 1u;
      if (b == 0) for (int i = t; i < (int)(offsetof(Flags, side) / 4); i += 64) ((uint32_t*)&g_fl)[i] = 0;
      uint32_t wv[7];
#pragma unroll
      for (int k = 0; k < 7; k++) wv[k] = ((const uint32_t*)gw)[k * 32 + lane];
#pragma unroll 4
      for (int r = w - 9; r < 16; r += 2) {
        const int tok = b * 16 + r;
        float s = 0.f;
#pragma unroll
        for (int k = 0; k < 7; k++) {
          const uint32_t v = ((const uint32_t*)(x + (size_t)tok * D))[k * 32 + lane];
          s = fmaf(bf_lo(v), bf_lo(wv[k]), fmaf(bf_hi(v), bf_hi(wv[k]), s));
        }
#pragma unroll
        for (int o = 16; o; o >>= 1) s += __shfl_xor_sync(0xffffffffu, s, o);
        if (lane == 0) g_gate[tok] = 1.f / (1.f + __expf(-s));
        const uint32_t id = (tok & 31) >> 1 == (lane & 15) ? ((tok & 1) ? 0x3f800000u : 0x00003f80u) : 0u;
        ((uint32_t*)(g_P + (size_t)tok * UROWS + UFFN))[lane] = id;
        ((uint32_t*)(g_P + (size_t)tok * UROWS + UFFN))[32 + lane] = id;
      }
    }
  }
}
namespace hp {
constexpr int W = 0;
constexpr int ST = W + 7 * 24576 + 32768;
constexpr int BAR = ST + 16384;
constexpr int FULL = BAR, EMPTY = BAR + 64, WB = BAR + 128;
constexpr int SIZE = BAR + 192;
constexpr int NSTG = 32 * 7;
}

template <int NS>
__device__ __forceinline__ void helper_release(uint32_t sb, int n) {
  if (n + NS < hp::NSTG) {
    mbar_arrive_tx(sb + hp::FULL + (n & (NS - 1)) * 8, 8192);
    mbar_arrive_remote(mapa(sb + hp::EMPTY + (n & (NS - 1)) * 8, (n + NS) % 7));
  }
}

template <int NHD>
__device__ __forceinline__ void helper_consumer(uint32_t sb, int wg, int h0, int r, const Maps* tm) {
  constexpr int NS = NHD == 3 ? 4 : 8, XR = hp::W + 7 * NHD * 8192;
  const int lane = threadIdx.x & 31, wq = (threadIdx.x >> 5) & 3, l7 = lane & 7, li = lane >> 3;
  const bool lead = (threadIdx.x & 127) == 0;
  int budget = 1 << 18;
  const uint32_t st = sb + hp::ST + wg * 8192, so = st + (16 * wq + l7 + 8 * (li & 1)) * 128;
  for (int t = wg; t < 32; t += 2) {
    float d[NHD * 32];
    if (t > 0) bar_sync(3 + wg, 256);
#pragma unroll 1
    for (int kb = 0; kb < 7; kb++) {
      const int n = 7 * t + kb;
      if (t < 2) mbar_wait(sb + hp::WB + kb * 8, 0, budget);
      mbar_wait(sb + hp::FULL + (n & (NS - 1)) * 8, (n / NS) & 1, budget);
      if (kb == 6 && t < 31) bar_arrive(3 + (wg ^ 1), 256);
      const uint64_t da0 = wdesc(sb + XR + (n & (NS - 1)) * 8192), db0 = wdesc(sb + hp::W + kb * NHD * 8192);
      wg_fence();
#pragma unroll
      for (int ks = 0; ks < 4; ks++) {
        const uint64_t da = da0 + ks * 2, db = db0 + ks * 2;
        if constexpr (NHD == 3) wgmma_n192<0, 0>(d, da, db, kb | ks); else wgmma_n128<0, 0>(d, da, db, kb | ks);
      }
      wg_commit();
      wg_wait<1>();
      if (kb > 0 && lead) helper_release<NS>(sb, n - 1);
      __syncwarp();
    }
    wg_wait<0>();
    if (lead) helper_release<NS>(sb, 7 * t + 6);
    __syncwarp();
    acc_fence(d);
    if (t == 0) pdl_launch();
#pragma unroll
    for (int i = 0; i < NHD; i++) {
      if (lead) bulk_wait_read0();
      bar_sync(1 + wg, 128);
#pragma unroll
      for (int k = 0; k < 8; k += 2) {
        const float* v = d + i * 32 + k * 4;
        stsm4(so + (((k + (li >> 1)) ^ l7) << 4), pack2(v[0], v[1]), pack2(v[2], v[3]), pack2(v[4], v[5]), pack2(v[6], v[7]));
      }
      fence_proxy_async_smem();
      bar_sync(1 + wg, 128);
      if (lead) {
        tma2d_store(&tm->u32, 64 * r, (2 * t) * UROWS + (h0 + i) * SEG, st);
        tma2d_store(&tm->u32, 64 * r, (2 * t + 1) * UROWS + (h0 + i) * SEG, st + 4096);
        bulk_commit();
      }
    }
    if (lead) { bulk_wait0(); red_relaxed(&g_fl.ux[t * 8 + r], 1); }
    __syncwarp();
  }
}

__device__ __forceinline__ void helper_producer(uint32_t sb, int h0, int nhd, int r, const Maps* tm) {
  int budget = 1 << 18;
  const int ns = nhd == 3 ? 4 : 8;
  const uint32_t xr = sb + hp::W + 7 * nhd * 8192;
  int n = r;
  if (n < ns) { if (elect()) tma2d_mc(xr + n * 8192, &tm->x64, 64 * r, 0, sb + hp::FULL + n * 8, 0x7f); n += 7; }
  for (int kb = 0; kb < 7; kb++)
    if (elect()) {
      const uint32_t dst = sb + hp::W + kb * nhd * 8192, bar = sb + hp::WB + kb * 8;
      mbar_arrive_tx(bar, nhd * 8192);
      tma2d(dst, &tm->v64, 64 * kb, h0 * D + 64 * r, bar);
      tma2d(dst + 8192, &tm->v64, 64 * kb, (h0 + 1) * D + 64 * r, bar);
      if (nhd == 3) tma2d(dst + 16384, &tm->v64, 64 * kb, (h0 + 2) * D + 64 * r, bar);
    }
  uint32_t ph = 0;
  for (; n < hp::NSTG; n += 7) {
    const int sl = n & (ns - 1);
    if (n >= ns) { mbar_wait(sb + hp::EMPTY + sl * 8, (ph >> sl) & 1, budget); ph ^= 1u << sl; }
    if (elect()) tma2d_mc(xr + sl * 8192, &tm->x64, 64 * r, 64 * (n / 7), sb + hp::FULL + sl * 8, 0x7f);
  }
}

__device__ __forceinline__ void helper_init(uint32_t sb, bool again = false) {
  if (threadIdx.x == 0) {
    if (again) for (int i = 0; i < 23; i++) asm volatile("mbarrier.inval.shared::cta.b64 [%0];" ::"r"(sb + hp::BAR + i * 8) : "memory");
    for (int i = 0; i < 8; i++) { mbar_init(sb + hp::FULL + i * 8, 1); mbar_init(sb + hp::EMPTY + i * 8, CL); }
    for (int i = 0; i < 7; i++) mbar_init(sb + hp::WB + i * 8, 1);
    asm volatile("fence.mbarrier_init.release.cluster;" ::: "memory");
    for (int i = 0; i < 8; i++) mbar_arrive_tx(sb + hp::FULL + i * 8, 8192);
  }
}

#define POLL_DELAY 27

namespace ch {
constexpr int UX = 0;
constexpr int XS = UX + 16384;
constexpr int MEM = XS + 8192;
constexpr int ST = MEM + 14336;
constexpr int W = ST + 6144;
constexpr int W0 = W + 14 * 8192;
constexpr int TB = W0 + 2 * 8192;
constexpr int UR = TB + 4096;
constexpr int RX = UR + 2048;
constexpr int SX = RX + 1536;
constexpr int SR = SX + 8960;
constexpr int PB = SR + 2560;
constexpr int PB2 = PB + 1280;
constexpr int BAR = PB2 + 1280;
constexpr int B_AG = BAR, B_SX = BAR + 48, B_RX = BAR + 56, B_X = BAR + 64, B_UX = BAR + 80, B_W = BAR + 96, B_ROLE = BAR + 104;
constexpr int B_P = BAR + 112;
constexpr int FLAG = BAR + 120;
constexpr int SIZE = BAR + 128;
constexpr int NB_SLICE = 1, NB_GO = 2, NB_SR = 3, NB_XW = 4, NB_UP = 5, NB_PUB = 6, NB_P2 = 7, NB_W = 8;
constexpr float SAFE = 60.f;
constexpr uint32_t AG_BYTES = 2 * 1024, SX_BYTES = 6 * 1280;
}

__device__ __forceinline__ void bar_sync_after(int id, uint32_t n, uint32_t x, uint32_t zero) {
  asm volatile("{.reg .b32 t; and.b32 t, %2, %3; add.u32 t, t, %1; bar.sync %0, t;}" ::"r"(id), "r"(n), "r"(x), "r"(zero) : "memory");
}
__device__ __forceinline__ uint32_t xor3(uint32_t a, uint32_t b, uint32_t c) {
  uint32_t o; asm("lop3.b32 %0, %1, %2, %3, 0x96;" : "=r"(o) : "r"(a), "r"(b), "r"(c)); return o;
}

template <int hf, int UR_>
__device__ __forceinline__ void chain_main_role(uint32_t sb, int c, int j, int tau, int lane, uint32_t zero, uint32_t side, uint32_t both, const Maps* tm) {
  int budget = 1 << 18;
  const int l7 = lane & 7, li = lane >> 3;
  uint32_t wo = sb + ch::W + (16 * tau + l7 + 8 * (li & 1)) * 128 + (((4 * hf + (li >> 1)) ^ l7) << 4);
  PIN(wo);
  uint32_t wa[7][2][2][4], wu[UR_ + 1][2][2][4];
  const int kw = tau + 4 * hf, kc = j - kw < 0 ? j - kw + CL : j - kw;
  if (elect()) {
    if (kw == 7) {
      mbar_arrive_tx(sb + ch::B_W, 16 * 8192);
      tma2d(sb + ch::W, &tm->v64, 64 * j, 2 * c * D + 64 * j, sb + ch::B_W);
      tma2d(sb + ch::W + 8192, &tm->v64, 64 * j, (2 * c + 1) * D + 64 * j, sb + ch::B_W);
    } else {
      const uint32_t dst = sb + (kw == 0 ? ch::W0 : ch::W + kw * 16384);
      tma2d(dst, &tm->a64, 64 * kc, 2 * c * D + 64 * j, sb + ch::B_W);
      tma2d(dst + 8192, &tm->a64, 64 * kc, (2 * c + 1) * D + 64 * j, sb + ch::B_W);
    }
  }
  mbar_wait(sb + ch::B_W, 0, budget);
#pragma unroll
  for (int k = 2; k < 14; k++) { ldsm4(wa[k >> 1][k & 1][0], wo + k * 8192); ldsm4(wa[k >> 1][k & 1][1], (wo ^ 32) + k * 8192); }
  bar_sync(ch::NB_W, 256);
  if (elect()) {
    if (kw == 7) mbar_arrive_tx(sb + ch::B_W, 12 * 8192);
    else if (kw > 0) {
      tma2d(sb + ch::W + kw * 16384, &tm->v64, 64 * kc, 2 * c * D + 64 * j, sb + ch::B_W);
      tma2d(sb + ch::W + kw * 16384 + 8192, &tm->v64, 64 * kc, (2 * c + 1) * D + 64 * j, sb + ch::B_W);
    }
  }
#pragma unroll
  for (int k = 8; k < 16 * UR_ + 16; k++) (&wu[0][0][0][0])[k] = 0;
  uint32_t l16_ = sb + lane * 16, lt_ = l16_ + tau * 512, wo_ = wo;
  uint32_t uo_ = sb + (l7 + 8 * (li & 1)) * 128 + (((2 * tau + (li >> 1)) ^ l7) << 4);
  PIN(l16_); PIN(lt_); PIN(uo_);
  const uint32_t ONES = 0x3f803f80u;
  int budgetP = 1 << 18;
  pdl_launch();

#pragma unroll 1
  for (int s = 0; s < NSEG; s++) {
    const uint32_t b = s & 1, ph = (s >> 1) & 1;
    const bool last = s == NSEG - 1;
    uint32_t l16 = l16_, lt = lt_, uo = uo_, wo = wo_;
    asm volatile("" : "+r"(l16), "+r"(lt), "+r"(uo), "+r"(wo));
    uint32_t ux[2][2][4] = {};
    char* r0 = nullptr;
    if (!hf) {
      if (s > 0 && !last) {
        mbar_wait(sb + ch::B_UX + b * 8, ph, budget);
#pragma unroll
        for (int i = 0; i < 4; i++) ldsm4t(ux[i >> 1][i & 1], uo + ch::UX + b * 8192 + i * 2048);
      }
      r0 = ring_page(b * 14 + 2 * j + (c >> 2), side) + ((c & 3) * 1024 + ((lt - l16) >> 1) + ((l16 - sb) >> 2));
    }
#pragma unroll
    for (int i = 0; i < 4; i++) {
      ldsm4(wa[0][i >> 1][i & 1], (wo ^ ((i & 1) << 5)) + (ch::W0 - ch::W) + (i >> 1) * 8192);
      ldsm4(wu[0][i >> 1][i & 1], (wo ^ ((i & 1) << 5)) + (i >> 1) * 8192);
    }
    if (hf) bar_sync(ch::NB_SLICE, 384); else bar_sync_after(ch::NB_SLICE, 384, (uint32_t)(uint64_t)r0, zero);
    uint32_t bb[7][4];
    float acc[2][2][4], au[2][4];
    const uint32_t ml = l16 + ch::MEM + hf * 512 + b * 7168;
    ldsm4(bb[0], ml);
#pragma unroll
    for (int k = 0; k < 7; k++) {
      if (k == 1 || k == 2 || k == 4) {
        const int k0 = k | 1;
        mbar_wait(sb + ch::B_AG + b * 24 + (k0 >> 1) * 8, ph, budget);
        ldsm4(bb[k0], ml + k0 * 1024);
        ldsm4(bb[k0 + 1], ml + (k0 + 1) * 1024);
      }
      {
#pragma unroll
        for (int hh = 0; hh < 2; hh++)
#pragma unroll
          for (int q = 0; q < 2; q++) {
            const uint32_t (&a)[4] = wa[k][hh][q];
            if (k == 0) mma16816_z(acc[hh][q], a[0], a[1], a[2], a[3], bb[k][2 * q], bb[k][2 * q + 1]);
            else mma16816(acc[hh][q], a[0], a[1], a[2], a[3], bb[k][2 * q], bb[k][2 * q + 1]);
          }
      }
      if (k == 0) {
#pragma unroll
        for (int i = 0; i < 4; i++) {
          const uint32_t (&a)[4] = wu[0][i >> 1][i & 1];
          if (i & 1) mma16816(au[i >> 1], a[0], a[1], a[2], a[3], bb[0][2], bb[0][3]);
          else mma16816_z(au[i >> 1], a[0], a[1], a[2], a[3], bb[0][0], bb[0][1]);
        }
      }
    }
    {
#pragma unroll
      for (int i = 0; i < 4; i++) { acc[0][0][i] += acc[0][1][i]; acc[1][0][i] += acc[1][1][i]; }
      stsm4t(lt + ch::TB + hf * 2048, pack2(acc[0][0][0], acc[0][0][1]), pack2(acc[1][0][0], acc[1][0][1]),
             pack2(acc[0][0][2], acc[0][0][3]), pack2(acc[1][0][2], acc[1][0][3]));
    }
    bar_arrive(ch::NB_XW, 384);
    if (s == 0) {
      mbar_wait(sb + ch::B_W, 1, budget);
#pragma unroll
      for (int k = 2; k < 2 * UR_ + 2; k++) { ldsm4(wu[k >> 1][k & 1][0], wo + k * 8192); ldsm4(wu[k >> 1][k & 1][1], (wo ^ 32) + k * 8192); }
    }
#pragma unroll
    for (int k = 1; k <= UR_; k++)
#pragma unroll
      for (int i = 0; i < 4; i++) {
        const uint32_t (&a)[4] = wu[k][i >> 1][i & 1];
        mma16816(au[i >> 1], a[0], a[1], a[2], a[3], bb[k][2 * (i & 1)], bb[k][2 * (i & 1) + 1]);
      }
    wo += (__float_as_uint(au[0][0]) | __float_as_uint(au[1][0])) & zero;
    if (!hf && s == 0) {
      mbar_wait(sb + ch::B_UX, 0, budget);
#pragma unroll
      for (int i = 0; i < 4; i++) ldsm4t(ux[i >> 1][i & 1], uo + ch::UX + i * 2048);
    }
    {
      uint32_t af[7][4][4];
#pragma unroll
      for (int k = UR_ + 1; k < UR_ + 1 + 2 && k < 7; k++)
#pragma unroll
        for (int i = 0; i < 4; i++) ldsm4(af[k][i], (wo ^ ((i & 1) << 5)) + (2 * k + (i >> 1)) * 8192);
#pragma unroll
      for (int k = UR_ + 1; k < 7; k++) {
        __syncwarp();
#pragma unroll
        for (int i = 0; i < 4; i++) {
          const uint32_t (&a)[4] = af[k][i];
          mma16816(au[i >> 1], a[0], a[1], a[2], a[3], bb[k][2 * (i & 1)], bb[k][2 * (i & 1) + 1]);
        }
        if (k + 2 < 7) {
#pragma unroll
          for (int i = 0; i < 4; i++) ldsm4(af[k + 2][i], (wo ^ ((i & 1) << 5)) + (2 * (k + 2) + (i >> 1)) * 8192);
        }
      }
    }
    const uint32_t um0 = pack2(au[0][0], au[0][1]), um1 = pack2(au[0][2], au[0][3]);
    const uint32_t um2 = pack2(au[1][0], au[1][1]), um3 = pack2(au[1][2], au[1][3]);
    if (hf) {
      sts128(lt + ch::UR, um0, um1, um2, um3);
      bar_arrive(ch::NB_UP, 256);
    } else {
      bar_sync(ch::NB_UP, 256);
      const uint4 v = lds128(lt + ch::UR);
      const uint32_t u0 = pack2(bf_lo(um0) + bf_lo(v.x), bf_hi(um0) + bf_hi(v.x)), u1 = pack2(bf_lo(um1) + bf_lo(v.y), bf_hi(um1) + bf_hi(v.y));
      const uint32_t u2 = pack2(bf_lo(um2) + bf_lo(v.z), bf_hi(um2) + bf_hi(v.z)), u3 = pack2(bf_lo(um3) + bf_lo(v.w), bf_hi(um3) + bf_hi(v.w));
      if (!last) {
        const uint32_t ta = (ph ^ 1u) << 16, to = ph << 16;
        char* r1 = (char*)((uint64_t)r0 ^ 4096);
        const uint32_t l8 = sb + ((l16 - sb) >> 1);
        uint32_t eo = l8 + ch::PB;
        mbar_wait(sb + ch::B_P, b | (xor3(u0, (uint32_t)(uint64_t)r1 ^ u1, xor3(eo, u2, u3)) & zero), budgetP);
        uint2 e[5];
#pragma unroll
        for (int k = 0; k < 5; k++) e[k] = lds64(eo + k * 256);
        uint32_t y0, y1;
        while (true) {
          const uint32_t bad = __any_sync(0xffffffffu, (int)(e[0].x | e[1].x | e[2].x | e[3].x | e[4].x) < 0);
          float l[4], o[2][2][4];
          mma16816_z(l, e[0].x, e[0].y, e[1].x, e[1].y, ONES, ONES);
#pragma unroll
          for (int i = 0; i < 4; i++) mma16816_z(o[i & 1][i >> 1], e[0].x, e[0].y, e[1].x, e[1].y, ux[i & 1][0][i & 2], ux[i & 1][0][(i & 2) + 1]);
          mma16816(l, e[2].x, e[2].y, e[3].x, e[3].y, ONES, ONES);
#pragma unroll
          for (int i = 0; i < 4; i++) mma16816(o[i & 1][i >> 1], e[2].x, e[2].y, e[3].x, e[3].y, ux[i & 1][1][i & 2], ux[i & 1][1][(i & 2) + 1]);
          mma1688(l, e[4].x, e[4].y, ONES);
          mma1688(o[0][0], e[4].x, e[4].y, u0); mma1688(o[1][0], e[4].x, e[4].y, u2);
          mma1688(o[0][1], e[4].x, e[4].y, u1); mma1688(o[1][1], e[4].x, e[4].y, u3);
          const float i0 = rcp(l[0]), i1 = rcp(l[2]);
          y0 = __byte_perm(((__float_as_uint(fmaf(o[1][0][2], i1, o[0][0][0] * i0)) + ta) & 0xFFFE0000u) | to,
                           pack2(0.f, fmaf(o[1][0][3], i1, o[0][0][1] * i0)), 0x7632);
          y1 = __byte_perm(((__float_as_uint(fmaf(o[1][1][2], i1, o[0][1][0] * i0)) + ta) & 0xFFFE0000u) | to,
                           pack2(0.f, fmaf(o[1][1][3], i1, o[0][1][1] * i0)), 0x7632);
          asm volatile("{.reg .pred p, q; setp.eq.u32 p, %4, 0; setp.ne.and.u32 q, %5, 0, p;\n"
                       "@q st.relaxed.gpu.global.b32 [%1], %2;\n @p st.relaxed.gpu.global.b32 [%0], %2;\n"
                       "@q st.relaxed.gpu.global.b32 [%1+128], %3;\n @p st.relaxed.gpu.global.b32 [%0+128], %3;}"
                       ::"l"(r0), "l"(r1), "r"(y0), "r"(y1), "r"(bad), "r"(both) : "memory");
          if (__builtin_expect(!bad, 1)) break;
          sts32(sb + ch::FLAG, s + 1);
          bar_arrive(ch::NB_GO, 256);
          bar_sync(ch::NB_P2, 256);
#pragma unroll
          for (int k = 0; k < 5; k++) e[k] = lds64(eo + (ch::PB2 - ch::PB) + k * 256);
        }
        bar_arrive(ch::NB_GO, 256);
      }
      stsm4t(uo + ch::ST + b * 3072, u0, u2, u1, u3);
      fence_proxy_async_smem();
      bar_arrive(ch::NB_PUB, 256);
    }
  }
}

__device__ __forceinline__ void chain_load_x(uint32_t sb, int s, int j, const Maps* tm) {
  const uint32_t bx = sb + ch::B_X + (s & 1) * 8;
  mbar_arrive_tx(bx, 4096);
  tma2d(sb + ch::XS + (s & 1) * 4096, &tm->x32, 64 * j, s * SEG, bx);
}
__device__ __forceinline__ void chain_load_ux(uint32_t sb, int s, int c, int j, const Maps* tm, uint32_t seen, int& budget) {
  const uint32_t bu = sb + ch::B_UX + (s & 1) * 8;
  if (seen < T_UX) flag_wait(&g_fl.ux[(s >> 1) * 8 + j], T_UX, budget);
  mbar_arrive_tx(bu, 8192);
  tma2d(sb + ch::UX + (s & 1) * 8192, &tm->u64, 64 * j, s * UROWS + 2 * c * SEG, bu);
}
__device__ __forceinline__ void chain_publish(uint32_t sb, int s, int c, int j, const Maps* tm) {
  tma2d_store(&tm->u16, 64 * j, s * UROWS + UMEM + 2 * c * MT, sb + ch::ST + (s & 1) * 3072);
  bulk_commit();
}
__device__ __forceinline__ void poll_issue(uint2 (&v)[NCH], const char* r0, const char* r1) {
#pragma unroll
  for (int k = 0; k < NCH; k++)
    asm volatile("ld.relaxed.gpu.global.v2.b32 {%0,%1}, [%2];" : "=r"(v[k].x), "=r"(v[k].y) : "l"((k < 4 ? r0 : r1) + (k & 3) * 1024) : "memory");
}
__device__ __forceinline__ bool poll_ok(const uint2 (&v)[NCH], uint32_t tag) {
  uint32_t o;
  asm volatile("{.reg .pred p; .reg .b32 a,b,c,d,e,f,g,h;\n"
      "lop3.b32 a,%1,%2,%17,0x7E; lop3.b32 b,%3,%4,%17,0x7E; lop3.b32 c,%5,%6,%17,0x7E; lop3.b32 d,%7,%8,%17,0x7E;\n"
      "lop3.b32 e,%9,%10,%17,0x7E; lop3.b32 f,%11,%12,%17,0x7E; lop3.b32 g,%13,%14,%17,0x7E; lop3.b32 h,%15,%16,%17,0x7E;\n"
      "lop3.b32 a,a,b,c,0xFE; lop3.b32 d,d,e,f,0xFE; lop3.b32 a,a,d,g,0xFE; lop3.b32 a,a,h,1,0xA8;\n"
      "setp.ne.u32 p, a, 0; vote.sync.any.pred p, p, 0xffffffff; selp.u32 %0, 0, 1, p;}"
      : "=r"(o) : "r"(v[0].x), "r"(v[0].y), "r"(v[1].x), "r"(v[1].y), "r"(v[2].x), "r"(v[2].y), "r"(v[3].x), "r"(v[3].y),
        "r"(v[4].x), "r"(v[4].y), "r"(v[5].x), "r"(v[5].y), "r"(v[6].x), "r"(v[6].y), "r"(v[7].x), "r"(v[7].y), "r"(tag));
  return o;
}
__device__ __forceinline__ void poll_sum(const uint2 (&v)[NCH], uint32_t ident, uint32_t& m0, uint32_t& m1) {
  float d0[4], d1[4];
  mma16816_z(d0, v[0].x, v[0].y, v[1].x, v[1].y, ident, ident);
  mma16816_z(d1, v[2].x, v[2].y, v[3].x, v[3].y, ident, ident);
  mma16816(d0, v[4].x, v[4].y, v[5].x, v[5].y, ident, ident);
  mma16816(d1, v[6].x, v[6].y, v[7].x, v[7].y, ident, ident);
  m0 = pack2(d0[0] + d1[0], d0[1] + d1[1]);
  m1 = pack2(d0[2] + d1[2], d0[3] + d1[3]);
}
__device__ __forceinline__ void sum7(float (&r)[4], const uint2 (&y)[CL], uint32_t ident) {
  float d[4] = {0.f, 0.f, 0.f, 0.f};
  mma1688(d, y[0].x, y[0].y, ident);
  mma16816_z(r, y[1].x, y[1].y, y[2].x, y[2].y, ident, ident);
  mma16816(d, y[3].x, y[3].y, y[4].x, y[4].y, ident, ident);
  mma16816(r, y[5].x, y[5].y, y[6].x, y[6].y, ident, ident);
#pragma unroll
  for (int i = 0; i < 4; i++) r[i] += d[i];
}

__device__ __forceinline__ void chain_safe_softmax(uint32_t sb, int j, uint32_t a, uint32_t lane, uint32_t par, uint32_t p0, uint32_t p1,
                                                uint32_t p2, uint32_t p3) {
  int budget = 1 << 18;
  const uint32_t l8 = sb + lane * 8, so = l8 + ch::SX, bar = sb + ch::B_SX;
  const uint32_t ident = (lane >> 3) == (lane & 3) ? ((lane & 4) ? 0x3f800000u : 0x00003f80u) : 0u;
  if (a == 0 && lane == 0) mbar_arrive_tx(bar, ch::SX_BYTES);
  __syncwarp();
  for (int p = 1; p < CL; p++) {
    const uint32_t r = j + p >= CL ? j + p - CL : j + p;
    stasync64(mapa(so + p * 1280 + a * 256, r), p0, p1, mapa(bar, r));
    if (a == 0) stasync64(mapa(so + p * 1280 + 1024, r), p2, p3, mapa(bar, r));
  }
  mbar_wait(bar, par, budget);
  uint2 y[CL], q[CL];
  y[0] = make_uint2(p0, p1); q[0] = make_uint2(p2, p3);
#pragma unroll
  for (int k = 1; k < CL; k++) { y[k] = lds64(so + k * 1280 + a * 256); q[k] = lds64(so + k * 1280 + 1024); }
  float rq[4], rm[4];
  sum7(rq, y, ident);
  sum7(rm, q, ident);
  sts64(l8 + ch::SR + a * 512, __float_as_uint(rq[0]), __float_as_uint(rq[1]));
  sts64(l8 + ch::SR + a * 512 + 256, __float_as_uint(rq[2]), __float_as_uint(rq[3]));
  bar_sync(ch::NB_SR, 128);
  if (a < 2) {
    float2 e[5];
#pragma unroll
    for (int k = 0; k < 4; k++) e[k] = lds64f(l8 + ch::SR + a * 256 + k * 512);
    e[4] = a ? make_float2(rm[2], rm[3]) : make_float2(rm[0], rm[1]);
    float m = fmaxf(fmaxf(fmaxf(e[0].x, e[0].y), fmaxf(e[1].x, e[1].y)), fmaxf(fmaxf(e[2].x, e[2].y), fmaxf(fmaxf(e[3].x, e[3].y), fmaxf(e[4].x, e[4].y))));
    m = fmaxf(m, __shfl_xor_sync(0xffffffffu, m, 1));
    m = fmaxf(m, __shfl_xor_sync(0xffffffffu, m, 2));
#pragma unroll
    for (int k = 0; k < 5; k++) sts32(l8 + ch::PB2 + k * 256 + a * 4, pack2(ex2(e[k].x - m), ex2(e[k].y - m)) & 0x7fff7fffu);
  }
  bar_arrive(ch::NB_P2, 256);
}

__device__ __forceinline__ void chain_aux_role(uint32_t sb, int c, int j, int a, int lane, uint32_t zero, uint32_t side, const bf16* mem0, const Maps* tm) {
  int budget = 1 << 18;
  if (a == 1 && lane == 0) { chain_load_x(sb, 0, j, tm); chain_load_x(sb, 1, j, tm); }
  __syncwarp();
  PIN(lane);
  const int lane_ = lane, a_ = a;
  const uint32_t rstep_ = mapa(sb, 1) - mapa(sb, 0), rself_ = mapa(sb, j) - sb;
  uint32_t p0 = 0, p1 = 0, p2 = 0, p3 = 0, nsafe = 0, uxSeen = 0;

#pragma unroll 1
  for (int s = 0; s < NSEG; s++) {
    const uint32_t b = s & 1, ph = (s >> 1) & 1;
    const bool last = s == NSEG - 1;
    uint32_t lane = lane_, a = a_, rstep = rstep_, rself = rself_;
    asm volatile("" : "+r"(lane), "+r"(a), "+r"(rstep), "+r"(rself));
    const uint32_t l8 = sb + lane * 8, l16 = sb + lane * 16;
    const uint32_t ident = (lane >> 3) == (lane & 3) ? ((lane & 4) ? 0x3f800000u : 0x00003f80u) : 0u;
    uint32_t mv0, mv1;
    {
      const uint32_t o = l8 + ch::MEM + b * 7168 + a * 256;
      uint32_t sa[6], sc[6];
#pragma unroll
      for (int p = 1; p < CL; p++) {
        const uint32_t dl = rself + (j + p >= CL ? p - CL : p) * rstep;
        sa[p - 1] = o + p * 1024 + dl; sc[p - 1] = sb + ch::B_AG + b * 24 + ((p - 1) >> 1) * 8 + dl;
      }
      if (s == 0) {
        const uint2 m = *(const uint2*)(mem0 + ((lane >> 1) & 7) * D + 64 * j + 16 * a + 8 * (lane >> 4) + 4 * (lane & 1));
        mv0 = m.x; mv1 = m.y;
      } else {
        const char* r0 = ring_page((b ^ 1) * 14 + 2 * j, side) + a * 256 + lane * 8;
        const char* r1 = ring_page((b ^ 1) * 14 + 2 * j + 1, side) + a * 256 + lane * 8;
        const uint32_t tag = ((s - 1) >> 1) & 1;
        uint2 A[NCH];
        bar_sync_after(ch::NB_GO, 256, xor3(xor3(xor3(sa[0], sa[1], sa[2]), xor3(sa[3], sa[4], sa[5]), xor3(sc[0], sc[1], sc[2])),
                                            xor3(sc[3], sc[4], sc[5]), xor3((uint32_t)(uint64_t)r0, (uint32_t)(uint64_t)r1, o)), zero);
        uint32_t fl = lds32(sb + ch::FLAG);
        if (__builtin_expect(fl == (uint32_t)s, 0)) {
          chain_safe_softmax(sb, j, a, lane, nsafe & 1, p0, p1, p2, p3);
          nsafe++;
          bar_sync(ch::NB_GO, 256);
        }
#pragma unroll
        for (int i = 0; i < POLL_DELAY; i++) asm volatile("mad.lo.u32 %0, %0, %0, %0;" : "+r"(fl));
        r0 += fl & zero; r1 += fl & zero;
        bool ok;
        do {
          poll_issue(A, r0, r1);
          poll_sum(A, ident, mv0, mv1);
          ok = poll_ok(A, tag);
        } while (!ok && --budget > 0);
      }
#pragma unroll
      for (int p = 0; p < 2; p++) stasync64(sa[p], mv0, mv1, sc[p]);
      sts64(o, mv0, mv1);
      bar_arrive(ch::NB_SLICE, 384);
#pragma unroll
      for (int p = 2; p < 6; p++) stasync64(sa[p], mv0, mv1, sc[p]);
    }
    if (c == 0) {
      const int tk = (lane >> 1) & 7;
      sts64(sb + ch::ST + b * 3072 + 2048 + tk * 128 + (((2 * a + (lane >> 4)) ^ tk) << 4) + (lane & 1) * 8, mv0, mv1);
      fence_proxy_async_smem();
    }
    if (s > 0) bar_sync(ch::NB_PUB, 256); else bar_sync(ch::NB_SR, 128);
    bool late = false;
    if (lane == 0) {
      if (a == 0) {
        if (s > 1) { bulk_wait0(); red_relaxed(&g_fl.um[s - 2], 1); }
        if (s > 0) chain_publish(sb, s - 1, c, j, tm);
      } else if (a == 1) {
        asm volatile("" : "+r"(uxSeen));
        late = s == 0 || uxSeen < T_UX;
        if (s > 0 && s + 1 < NSEG - 1) { chain_load_x(sb, s + 1, j, tm); if (!late) chain_load_ux(sb, s + 1, c, j, tm, T_UX, budget); }
        uxSeen = ld_relaxed(&g_fl.ux[((s + 2) >> 1 & 31) * 8 + j + (late ? zero : 0)]);
      } else if (a == 2) {
        if (s > 0 && s + 1 < NSEG) {
          mbar_arrive_tx(sb + ch::B_AG + (b ^ 1) * 24, ch::AG_BYTES);
          mbar_arrive_tx(sb + ch::B_AG + (b ^ 1) * 24 + 8, ch::AG_BYTES);
          mbar_arrive_tx(sb + ch::B_AG + (b ^ 1) * 24 + 16, ch::AG_BYTES);
        }
        if (!last) { mbar_arrive_tx(sb + ch::B_P, 1280); if (j < 5) mbar_arrive_tx(sb + ch::B_RX, 1536); }
      } else if (c == 0) {
        if (s > 0) { bulk_wait0(); red_relaxed(&g_fl.mem[s - 1], 1); }
        tma2d_store(&tm->m8, 64 * j, s * MT, sb + ch::ST + b * 3072 + 2048);
        bulk_commit();
        if (last) { bulk_wait0(); red_relaxed(&g_fl.mem[s], 1); }
      }
    }
    __syncwarp();
    if (last) {
      bar_sync(ch::NB_XW, 384);
      break;
    }
    const int sl = j - (int)a, s4 = j - 4;
    const uint32_t da = rself - sl * rstep, d4 = rself - s4 * rstep;
    const uint32_t ra = l8 + ch::RX - 256 + (sl < 0 ? sl + CL : sl) * 256 + da, rb = sb + ch::B_RX + da;
    const uint32_t rc = l8 + ch::RX - 256 + (s4 < 0 ? s4 + CL : s4) * 256 + d4, rd = sb + ch::B_RX + d4;
    uint32_t ba[CL], bc[CL];
#pragma unroll
    for (int p = 0; p < CL; p++) {
      const int q = p == CL - 1 ? 0 : p + 1;
      const uint32_t dl = rself + (j + q >= CL ? q - CL : q) * rstep;
      ba[p] = l8 + ch::PB + j * 256 + dl; bc[p] = sb + ch::B_P + dl;
    }
    uint32_t xk[2][4], mk[2][4];
    mbar_wait(sb + ch::B_X + b * 8, ph, budget);
    {
      const uint32_t xo = sb + ch::XS + b * 4096 + (8 * a + (lane & 7)) * 128 + (((lane >> 3) ^ (lane & 7)) << 4);
      ldsm4(xk[0], xo); ldsm4(xk[1], xo ^ 64);
      ldsm4(mk[0], l16 + ch::MEM + b * 7168); ldsm4(mk[1], l16 + ch::MEM + b * 7168 + 512);
    }
    const uint32_t anchor = xor3(xor3(xor3(ra, rb, rc), rd, l16), xor3(xor3(ba[0], ba[1], ba[2]), xor3(ba[3], ba[4], ba[5]), xor3(ba[6], bc[0], bc[1])),
                                 xor3(xor3(bc[2], bc[3], bc[4]), bc[5], bc[6])) & zero;
    bar_sync_after(ch::NB_XW, 384, anchor, zero);
    {
      uint32_t ta[8][4];
#pragma unroll
      for (int k = 0; k < 8; k++) ldsm4(ta[(k >> 1) + 4 * (k & 1)], l16 + ch::TB + ((k >> 1) + 4 * (k & 1)) * 512);
      float sq[2][4], sm[2][4];
#pragma unroll
      for (int k = 0; k < 4; k++)
#pragma unroll
        for (int h = 0; h < 2; h++) {
          const uint32_t (&t)[4] = ta[k + 4 * h];
          if (k == 0) {
            mma16816_z(sq[h], t[0], t[1], t[2], t[3], xk[0][0], xk[0][1]);
            mma16816_z(sm[h], t[0], t[1], t[2], t[3], mk[0][0], mk[0][1]);
          } else {
            mma16816(sq[h], t[0], t[1], t[2], t[3], xk[k >> 1][2 * (k & 1)], xk[k >> 1][2 * (k & 1) + 1]);
            mma16816(sm[h], t[0], t[1], t[2], t[3], mk[k >> 1][2 * (k & 1)], mk[k >> 1][2 * (k & 1) + 1]);
          }
        }
      p0 = pack2(sq[0][0] + sq[1][0], sq[0][1] + sq[1][1]); p1 = pack2(sq[0][2] + sq[1][2], sq[0][3] + sq[1][3]);
      p2 = pack2(sm[0][0] + sm[1][0], sm[0][1] + sm[1][1]); p3 = pack2(sm[0][2] + sm[1][2], sm[0][3] + sm[1][3]);
    }
    if (sl != 0) stasync64(ra, p0, p1, rb);
    if (a == (j < 4 ? j : 3) && s4 != 0) stasync64(rc, p2, p3, rd);
    if (j < 4 ? sl == 0 : (j == 4 && a == 0)) {
      uint2 y[CL];
      y[0] = j < 4 ? make_uint2(p0, p1) : make_uint2(p2, p3);
      mbar_wait(sb + ch::B_RX, b, budget);
#pragma unroll
      for (int k = 1; k < CL; k++) y[k] = lds64(l8 + ch::RX + (k - 1) * 256);
      float r[4];
      sum7(r, y, ident);
      const uint32_t mark = fmaxf(fmaxf(fabsf(r[0]), fabsf(r[1])), fmaxf(fabsf(r[2]), fabsf(r[3]))) <= ch::SAFE ? 0u : 0x80000000u;
      const uint32_t e0 = pack2(ex2(r[0]), ex2(r[1])) | mark, e1 = pack2(ex2(r[2]), ex2(r[3]));
#pragma unroll
      for (int p = 0; p < CL; p++) stasync64(ba[p], e0, e1, bc[p]);
    }
    if (__builtin_expect(late, 0)) {
      if (s == 0) chain_load_ux(sb, 0, c, j, tm, 0, budget);
      if (s + 1 < NSEG - 1) chain_load_ux(sb, s + 1, c, j, tm, 0, budget);
    }
    __syncwarp();
  }
  bar_sync(ch::NB_PUB, 256);
  if (a == 0 && lane == 0) {
    bulk_wait0(); red_relaxed(&g_fl.um[NSEG - 2], 1);
    chain_publish(sb, NSEG - 1, c, j, tm);
    bulk_wait0(); red_relaxed(&g_fl.um[NSEG - 1], 1);
  }
  __syncwarp();
}

__device__ __forceinline__ void chain_init(uint32_t sb) {
  if (threadIdx.x == 0) {
    for (int i = 0; i < 15; i++) mbar_init(sb + ch::BAR + i * 8, 1);
    sts32(sb + ch::FLAG, 0);
    asm volatile("fence.mbarrier_init.release.cluster;" ::: "memory");
    for (int i = 0; i < 6; i++) mbar_arrive_tx(sb + ch::B_AG + i * 8, ch::AG_BYTES);
    mbar_arrive_tx(sb + ch::B_ROLE, 4);
  }
}
namespace wk {
constexpr int A = 0;
constexpr int B = A + 7 * 16384;
constexpr int ST = B + 3 * 32768;
constexpr int BAR = ST + 16384;
constexpr int AF = BAR, AE = BAR + 56, BF = BAR + 112, BE = BAR + 136, MF = BAR + 160, IF = BAR + 192, IE = BAR + 208, ITEM = BAR + 224, PS = BAR + 232;
constexpr int UF = BAR + 264, UE = BAR + 344;
constexpr int SIZE = BAR + 424;
#define NPAIR_ 12
#define LAG_ 5
constexpr int NPAIR = NPAIR_, LAG = LAG_;
constexpr int E0 = 64, E1 = E0 + LAG * 8, E2 = E1 + (NPAIR - LAG) * 12, E3 = E2 + (16 - NPAIR) * 20, NITEM = E3 + LAG * 28;
enum { FF, PA, PB, END };
}

__device__ __forceinline__ void item_decode(int it, int& type, int& tile, int& sub, int& nh) {
  int npa = 8;
  nh = 1;
  if (it >= wk::NITEM) { type = wk::END; tile = sub = 0; return; }
  if (it < wk::E0) { type = wk::FF; tile = it >> 2; sub = it & 3; return; }
  if (it < wk::E1) { it -= wk::E0; tile = it >> 3; it &= 7; }
  else if (it < wk::E2) { it -= wk::E1; tile = wk::LAG + it / 12; it %= 12; }
  else if (it < wk::E3) { it -= wk::E2; tile = wk::NPAIR + it / 20; it %= 20; npa = 16; }
  else {
    it -= wk::E3 + 7;
    if (it < 0) it += wk::LAG * 28;
    tile = 16 + it / 28; it %= 28; npa = 0;
  }
  if (it < npa) { type = wk::PA; nh = npa == 8 ? 2 : 1; sub = it * nh; }
  else { type = wk::PB; nh = npa ? 7 : 1; sub = (it - npa) * nh; tile -= wk::LAG; }
}

struct Prod {
  uint32_t sb, aph = 0, bs = 0, bph = 0, us = 0, uph = 0;
  int budget = 1 << 20;
  __device__ __forceinline__ void a_free(int s) { mbar_wait(sb + wk::AE + s * 8, ((aph >> s) & 1) ^ 1, budget); aph ^= 1u << s; }
  __device__ __forceinline__ int b_free() {
    const int s = bs;
    mbar_wait(sb + wk::BE + s * 8, bph ^ 1, budget);
    if (++bs == 3) { bs = 0; bph ^= 1; }
    return s;
  }
  __device__ __forceinline__ void flag(const uint32_t* p, uint32_t target) {
    while (ld_acquire(p) < target && --budget > 0) __nanosleep(32);
  }
};

__device__ __forceinline__ void work_producer(uint32_t sb, const WorkMaps* tm) {
  Prod p; p.sb = sb;
  {
    const uint32_t n0 = ld_relaxed(&g_fl.side[0]), n1 = ld_relaxed(&g_fl.side[1]);
    const uint32_t side = ld_relaxed(&g_side[smid()]);
    __syncwarp();
    g_side[smid()] = 2;
    if (side == (n1 > n0 ? 1u : 0u))
      while (ld_relaxed(&g_fl.mem[POLITE]) < T_MEM && --p.budget > 0) __nanosleep(500);
  }
  for (uint32_t n = 0;; n++) {
    int it = 0;
    if ((threadIdx.x & 31) == 0) it = atomicAdd(&g_fl.queue, 1);
    it = __reduce_max_sync(0xffffffffu, it);
    mbar_wait(sb + wk::IE + (n & 1) * 8, ((n >> 1) & 1) ^ 1, p.budget);
    if (elect()) { sts32(sb + wk::ITEM + (n & 1) * 4, it); mbar_arrive(sb + wk::IF + (n & 1) * 8); }
    int type, tile, sub, nh;
    item_decode(it, type, tile, sub, nh);
    if (type == wk::END) break;
    if (type == wk::PB) {
      const int seg = 4 * tile + sub / 7, mb0 = sub % 7, l = threadIdx.x & 15;
      const uint32_t* fp = l == 0 ? &g_fl.f[tile] : l == 1 ? &g_fl.um[seg] : l == 2 ? &g_fl.p[seg] : &g_fl.ux[(seg >> 1) * 8 + min(mb0 + l - 3, mb0 + nh - 1)];
      const bool ready = __all_sync(0xffffffffu, ld_acquire(fp) >= (l == 0 ? T_F : l == 1 ? T_UM : l == 2 ? T_P : T_UX));
      if (ready) fence_proxy_async();
#pragma unroll 1
      for (int a = 3; a < 7; a++) { p.a_free(a); if (elect()) mbar_arrive(sb + wk::AF + a * 8); }
#pragma unroll 1
      for (int a = 0; a < 3; a++) { const int q = p.b_free(); if (elect()) mbar_arrive(sb + wk::BF + q * 8); }
#pragma unroll 1
      for (int mb = mb0; mb < mb0 + nh; mb++) {
        if (!ready) p.flag(&g_fl.ux[(seg >> 1) * 8 + mb], T_UX);
#pragma unroll 1
        for (int u = 0; u < 6; u++) {
          mbar_wait(sb + wk::UE + p.us * 8, p.uph ^ 1, p.budget);
          if (!ready && mb == mb0 && u >= 3 && u != 4) p.flag(u == 5 ? &g_fl.um[seg] : &g_fl.f[tile], u == 5 ? T_UM : T_F);
          if (elect()) {
            mbar_arrive_tx(sb + wk::UF + p.us * 8, 16384);
            tma2d(sb + wk::A + (3 + p.us) * 16384, &tm->u128, 64 * mb, seg * UROWS + 128 * ((0x425130 >> (4 * u)) & 7), sb + wk::UF + p.us * 8);
          }
          if (++p.us == 10) { p.us = 0; p.uph ^= 1; }
        }
        if (mb == mb0) {
#pragma unroll 1
          for (int a = 0; a < 3; a++) p.a_free(a);
          if (!ready) { p.flag(&g_fl.p[seg], T_P); fence_proxy_async(); }
          if (elect()) {
            for (int a = 0; a < 3; a++) {
              mbar_arrive_tx(sb + wk::AF + a * 8, 16384);
              tma3d(sb + wk::A + a * 16384, &tm->p3, 0, SEG * seg, 4 * a, sb + wk::AF + a * 8);
            }
          }
        }
      }
    } else {
      for (int hh = 0; hh < nh; hh++) {
#pragma unroll 1
        for (int pass = 0; pass < 2; pass++)
#pragma unroll 1
          for (int kb = 0; kb < 7; kb++) {
            if (pass == 0 && hh == 0) {
              p.a_free(kb);
              if (elect()) {
                mbar_arrive_tx(sb + wk::AF + kb * 8, 16384);
                tma2d(sb + wk::A + kb * 16384, &tm->x128, 64 * kb, 128 * tile, sb + wk::AF + kb * 8);
              }
            }
            const int s = p.b_free();
            if (elect()) {
              const uint32_t bar = sb + wk::BF + s * 8, dst = sb + wk::B + s * 32768;
              mbar_arrive_tx(bar, pass ? 24576 : 32768);
              if (type == wk::PA) tma2d(dst, pass ? &tm->a192 : &tm->a256, 64 * kb, (sub + hh) * D + 256 * pass, bar);
              else tma3d(dst, pass ? &tm->w1b : &tm->w1a, 0, 64 * kb, 7 * sub + 4 * pass, bar);
            }
          }
        if (type == wk::PA) {
          const int s = p.b_free();
          if (elect()) mbar_arrive(sb + wk::BF + s * 8);
          bool ready = hh > 0;
          if (!ready) { ready = ld_acquire(&g_fl.mem[4 * tile + (threadIdx.x & 3)]) >= T_MEM;
                        ready = __all_sync(0xffffffffu, ready); }
#pragma unroll 1
          for (int i = 0; i < 4; i++) {
            if (!ready) p.flag(&g_fl.mem[4 * tile + i], T_MEM);
            if (elect()) {
              mbar_arrive_tx(sb + wk::MF + i * 8, MT * D * 2);
              tma3d(sb + wk::B + s * 32768 + i * 7168, &tm->m3, 0, (4 * tile + i) * MT, 0, sb + wk::MF + i * 8);
            }
          }
        } else {
#pragma unroll 1
          for (int g = 0; g < 26; g += 2) {
            const int s = p.b_free();
            if (elect()) {
              const uint32_t bar = sb + wk::BF + s * 8, dst = sb + wk::B + s * 32768;
              mbar_arrive_tx(bar, g == 20 ? 16384 : g == 24 ? 24576 : 32768);
              if (g < 21) tma3d(dst, &tm->w2b, 0, D * sub + 64 * (g % 7), 2 * (g / 7), bar);
              if (g < 20) tma3d(dst + 16384, &tm->w2b, 0, D * sub + 64 * ((g + 1) % 7), 2 * ((g + 1) / 7), bar);
              if (g > 20) tma2d(dst, g == 22 ? &tm->w2c : &tm->w2d, 384, D * sub + (g == 22 ? 0 : 256), bar);
            }
          }
        }
      }
    }
  }
}

struct Cons {
  uint32_t sb, aph = 0, bs = 0, bph = 0, mph = 0, us = 0, uph = 0;
  int budget = 1 << 20, wg, wq, lane;
  bool lead;
  __device__ __forceinline__ void a_wait(int s) { mbar_wait(sb + wk::AF + s * 8, (aph >> s) & 1, budget); aph ^= 1u << s; }
  __device__ __forceinline__ void a_rel(int s) { if (lead) mbar_arrive(sb + wk::AE + s * 8); }
  __device__ __forceinline__ int b_wait() {
    const int s = bs;
    mbar_wait(sb + wk::BF + s * 8, bph, budget);
    if (++bs == 3) { bs = 0; bph ^= 1; }
    return s;
  }
  __device__ __forceinline__ void b_rel(int s) { if (lead) mbar_arrive(sb + wk::BE + s * 8); }
};

template <int NB, int TB, bool AREL>
__device__ __forceinline__ void gemm_pass(Cons& c, float (&d)[NB * 32], bool await) {
#pragma unroll
  for (int i = 0; i < NB * 32; i++) d[i] = 0.f;
#pragma unroll 1
  for (int kb = 0; kb < 7; kb++) {
    if (await) c.a_wait(kb);
    const int s = c.b_wait();
    const uint64_t da0 = wdesc(c.sb + wk::A + kb * 16384 + c.wg * 8192), db0 = wdesc(c.sb + wk::B + s * 32768);
    wg_fence();
#pragma unroll
    for (int ks = 0; ks < 4; ks++) {
      const uint64_t da = da0 + ks * 2, db = db0 + ks * (TB ? 128 : 2);
      if constexpr (NB == 4) wgmma_n256<0, TB>(d, da, db, 1); else wgmma_n192<0, TB>(d, da, db, 1);
    }
    wg_commit();
    wg_wait<0>();
    c.b_rel(s);
    if (AREL) c.a_rel(kb);
    __syncwarp();
  }
  acc_fence(d);
}

template <int P>
__device__ __forceinline__ void ffn_pass(Cons& c, const uint32_t (&tp)[112], int& cur, int tile, int chunk, const WorkMaps* tm) {
  constexpr int NB = P < 3 ? 2 : 1, col0 = 128 * P;
  float d[NB * 32];
#pragma unroll
  for (int i = 0; i < NB * 32; i++) d[i] = 0.f;
#pragma unroll
  for (int kb = 0; kb < 7; kb++) {
    const int g = 7 * P + kb;
    if (P < 3 ? !(g & 1) : !(kb & 3)) cur = c.b_wait();
    const uint64_t db = wdesc(c.sb + wk::B + cur * 32768 + (P < 3 ? (g & 1) * 16384 : (kb & 3) * 8192));
    wg_fence();
#pragma unroll
    for (int ks = 0; ks < 4; ks++) {
      if constexpr (NB == 2) wgmma_rs_n128<1>(d, &tp[16 * kb + 4 * ks], db + ks * 128); else wgmma_rs_n64<1>(d, &tp[16 * kb + 4 * ks], db + ks * 128);
    }
    wg_commit();
    if (P < 3 ? ((g & 1) || g == 20) : (kb == 3 || kb == 6)) { wg_wait<0>(); c.b_rel(cur); __syncwarp(); }
  }
  wg_wait<0>();
  acc_fence(d);
  const int l7 = c.lane & 7, li = c.lane >> 3;
  const uint32_t st = c.sb + wk::ST + c.wg * 8192, so = st + (16 * c.wq + l7 + 8 * (li & 1)) * 128;
#pragma unroll
  for (int i = 0; i < NB; i++) {
    if (c.lead) bulk_wait_read0();
    bar_sync(1 + c.wg, 128);
#pragma unroll
    for (int k = 0; k < 8; k += 2) {
      const float* v = d + i * 32 + k * 4;
      stsm4(so + (((k + (li >> 1)) ^ l7) << 4), pack2(v[0], v[1]), pack2(v[2], v[3]), pack2(v[4], v[5]), pack2(v[6], v[7]));
    }
    fence_proxy_async_smem();
    bar_sync(1 + c.wg, 128);
    if (c.lead) {
      tma2d_store(&tm->u32, col0 + 64 * i, (4 * tile + 2 * c.wg) * UROWS + UFFN + SEG * chunk, st);
      tma2d_store(&tm->u32, col0 + 64 * i, (4 * tile + 2 * c.wg + 1) * UROWS + UFFN + SEG * chunk, st + 4096);
      bulk_commit();
    }
  }
}

template <bool UPPER>
__device__ __forceinline__ void attn_rows(Cons& c, const uint32_t (&tp)[112], int tile, int h, bool arel) {
  constexpr int NX = UPPER ? 4 : 2;
  const int lane = c.lane, l7 = lane & 7, li = lane >> 3, g = lane >> 2, t = lane & 3, sl = c.wq >> 1;
  float sx[NX][4], sm[4][4];
  const uint32_t xo = c.sb + wk::A + c.wg * 8192 + (32 * sl + l7 + 8 * (li >> 1)) * 128 + (((li & 1) ^ l7) << 4);
#pragma unroll
  for (int k = 0; k < 28; k++) {
    uint32_t xa[4];
#pragma unroll
    for (int hf = 0; hf < NX / 2; hf++) {
      ldsm4(xa, (xo ^ ((k & 3) << 5)) + (k >> 2) * 16384 + hf * 2048);
      if (k == 0) {
        mma16816_z(sx[2 * hf], tp[0], tp[1], tp[2], tp[3], xa[0], xa[1]);
        mma16816_z(sx[2 * hf + 1], tp[0], tp[1], tp[2], tp[3], xa[2], xa[3]);
      } else {
        mma16816(sx[2 * hf], tp[4 * k], tp[4 * k + 1], tp[4 * k + 2], tp[4 * k + 3], xa[0], xa[1]);
        mma16816(sx[2 * hf + 1], tp[4 * k], tp[4 * k + 1], tp[4 * k + 2], tp[4 * k + 3], xa[2], xa[3]);
      }
    }
  }
  if (arel) {
    bar_sync(1 + c.wg, 128);
#pragma unroll
    for (int k = 0; k < 7; k++) c.a_rel(k);
  }
  const int tok = 128 * tile + 64 * c.wg + 16 * c.wq + g;
  const float g0 = g_gate[tok], g1 = g_gate[tok + 8];
  const int s = c.b_wait();
  mbar_wait(c.sb + wk::MF + (2 * c.wg + sl) * 8, c.mph, c.budget);
  c.mph ^= 1;
  const uint32_t mo = c.sb + wk::B + s * 32768 + (2 * c.wg + sl) * 7168 + l7 * 128 + ((li ^ l7) << 4);
#pragma unroll
  for (int k = 0; k < 14; k++) {
    uint32_t ma[4];
    ldsm4(ma, (mo ^ ((k & 1) << 6)) + (k >> 1) * 1024);
    if (k < 2) {
      mma16816_z(sm[2 * (k & 1)], tp[8 * k], tp[8 * k + 1], tp[8 * k + 2], tp[8 * k + 3], ma[0], ma[1]);
      mma16816_z(sm[2 * (k & 1) + 1], tp[8 * k + 4], tp[8 * k + 5], tp[8 * k + 6], tp[8 * k + 7], ma[2], ma[3]);
    } else {
      mma16816(sm[2 * (k & 1)], tp[8 * k], tp[8 * k + 1], tp[8 * k + 2], tp[8 * k + 3], ma[0], ma[1]);
      mma16816(sm[2 * (k & 1) + 1], tp[8 * k + 4], tp[8 * k + 5], tp[8 * k + 6], tp[8 * k + 7], ma[2], ma[3]);
    }
  }
#pragma unroll
  for (int i = 0; i < 4; i++) sm[0][i] = (sm[0][i] + sm[1][i]) + (sm[2][i] + sm[3][i]);
  const float NEG = -INFINITY;
  if (2 * t > g) { sx[NX - 2][0] = NEG; sx[NX - 1][2] = NEG; }
  if (2 * t + 1 > g) { sx[NX - 2][1] = NEG; sx[NX - 1][3] = NEG; }
  sx[NX - 1][0] = NEG; sx[NX - 1][1] = NEG;
  float m0 = fmaxf(sm[0][0], sm[0][1]), m1 = fmaxf(sm[0][2], sm[0][3]);
#pragma unroll
  for (int q = 0; q < NX; q++) { m0 = fmaxf(m0, fmaxf(sx[q][0], sx[q][1])); m1 = fmaxf(m1, fmaxf(sx[q][2], sx[q][3])); }
  m0 = fmaxf(m0, __shfl_xor_sync(0xffffffffu, m0, 1)); m1 = fmaxf(m1, __shfl_xor_sync(0xffffffffu, m1, 1));
  m0 = fmaxf(m0, __shfl_xor_sync(0xffffffffu, m0, 2)); m1 = fmaxf(m1, __shfl_xor_sync(0xffffffffu, m1, 2));
  sm[0][0] = ex2(sm[0][0] - m0); sm[0][1] = ex2(sm[0][1] - m0); sm[0][2] = ex2(sm[0][2] - m1); sm[0][3] = ex2(sm[0][3] - m1);
  float l0 = sm[0][0] + sm[0][1], l1 = sm[0][2] + sm[0][3];
#pragma unroll
  for (int q = 0; q < NX; q++) {
    sx[q][0] = ex2(sx[q][0] - m0); sx[q][1] = ex2(sx[q][1] - m0); sx[q][2] = ex2(sx[q][2] - m1); sx[q][3] = ex2(sx[q][3] - m1);
    l0 += sx[q][0] + sx[q][1]; l1 += sx[q][2] + sx[q][3];
  }
  l0 += __shfl_xor_sync(0xffffffffu, l0, 1); l1 += __shfl_xor_sync(0xffffffffu, l1, 1);
  l0 += __shfl_xor_sync(0xffffffffu, l0, 2); l1 += __shfl_xor_sync(0xffffffffu, l1, 2);
  const float r0 = g0 / l0, r1 = g1 / l1;
  uint32_t* p0 = (uint32_t*)(g_P + (size_t)tok * UROWS) + t;
  uint32_t* p1 = p0 + 8 * UROWS / 2;
  p0[(UMEM + h * MT) / 2] = pack2(sm[0][0] * r0, sm[0][1] * r0); p1[(UMEM + h * MT) / 2] = pack2(sm[0][2] * r1, sm[0][3] * r1);
#pragma unroll
  for (int q = 0; q < 4; q++) {
    p0[h * 16 + 4 * q] = q < NX ? pack2(sx[q < NX ? q : 0][0] * r0, sx[q < NX ? q : 0][1] * r0) : 0u;
    p1[h * 16 + 4 * q] = q < NX ? pack2(sx[q < NX ? q : 0][2] * r1, sx[q < NX ? q : 0][3] * r1) : 0u;
  }
  __syncwarp();
  if (lane == 0) mbar_arrive(c.sb + wk::PS + (2 * c.wg + sl) * 8);
  bar_sync(1 + c.wg, 128);
  c.b_rel(s);
  __syncwarp();
}

__device__ __forceinline__ void work_consumer(uint32_t sb, const WorkMaps* tm) {
  Cons c;
  c.sb = sb; c.wg = __reduce_max_sync(0xffffffffu, threadIdx.x >> 7); c.wq = __reduce_max_sync(0xffffffffu, (threadIdx.x >> 5) & 3); c.lane = threadIdx.x & 31; c.lead = (threadIdx.x & 127) == 0;
  for (uint32_t n = 0;; n++) {
    mbar_wait(sb + wk::IF + (n & 1) * 8, (n >> 1) & 1, c.budget);
    const int it = __reduce_max_sync(0xffffffffu, c.budget > 0 ? (int)lds32(sb + wk::ITEM + (n & 1) * 4) : wk::NITEM);
    if (c.lane == 0) mbar_arrive(sb + wk::IE + (n & 1) * 8);
    int type, tile, sub, nh;
    item_decode(it, type, tile, sub, nh);
    if (type == wk::END) break;
    if (type == wk::PA) {
#pragma unroll 1
      for (int hh = 0; hh < nh; hh++) {
        uint32_t tp[112];
        {
          float d[128];
          gemm_pass<4, 0, false>(c, d, hh == 0);
#pragma unroll
          for (int i = 0; i < 64; i++) tp[i] = pack2(d[2 * i], d[2 * i + 1]);
        }
        {
          float d[96];
          gemm_pass<3, 0, false>(c, d, false);
#pragma unroll
          for (int i = 0; i < 48; i++) tp[64 + i] = pack2(d[2 * i], d[2 * i + 1]);
        }
        if (c.wq & 1) attn_rows<true>(c, tp, tile, sub + hh, hh == nh - 1); else attn_rows<false>(c, tp, tile, sub + hh, hh == nh - 1);
      }
    } else if (type == wk::FF) {
      const int tok = 128 * tile + 64 * c.wg + 16 * c.wq + (c.lane >> 2);
      const float s0 = 1.f - g_gate[tok], s1 = 1.f - g_gate[tok + 8];
      uint32_t tp[112];
      {
        float d[128];
        gemm_pass<4, 1, false>(c, d, true);
#pragma unroll
        for (int i = 0; i < 64; i++) tp[i] = pack2(fmaxf(d[2 * i], 0.f) * (i & 1 ? s1 : s0), fmaxf(d[2 * i + 1], 0.f) * (i & 1 ? s1 : s0));
      }
      {
        float d[96];
        gemm_pass<3, 1, true>(c, d, false);
#pragma unroll
        for (int i = 0; i < 48; i++) tp[64 + i] = pack2(fmaxf(d[2 * i], 0.f) * (i & 1 ? s1 : s0), fmaxf(d[2 * i + 1], 0.f) * (i & 1 ? s1 : s0));
      }
      int cur = 0;
      ffn_pass<0>(c, tp, cur, tile, sub, tm);
      ffn_pass<1>(c, tp, cur, tile, sub, tm);
      ffn_pass<2>(c, tp, cur, tile, sub, tm);
      ffn_pass<3>(c, tp, cur, tile, sub, tm);
      if (c.lead) { bulk_wait0(); red_relaxed(&g_fl.f[tile], 1); }
      __syncwarp();
    } else {
      const int seg = 4 * tile + sub / 7, mb0 = sub % 7;
      for (int a = 3; a < 7; a++) c.a_wait(a);
      for (int a = 0; a < 3; a++) c.b_wait();
      for (int a = 0; a < 3; a++) c.a_wait(a);
#pragma unroll 1
      for (int mb = mb0; mb < mb0 + nh; mb++) {
      float d[16];
#pragma unroll
      for (int i = 0; i < 16; i++) d[i] = 0.f;
#pragma unroll 1
      for (int j = 0; j < 3; j++) {
        uint32_t u = c.us + c.wg, ph = c.uph;
        mbar_wait(sb + wk::UF + u * 8, ph, c.budget);
        const uint64_t da = wdesc(sb + wk::A + (3 + u) * 16384), db = wdesc(sb + wk::A + (c.wg == 0 ? j : j == 0 ? 3 : 6 - j) * 8192);
        wg_fence();
#pragma unroll
        for (int ks = 0; ks < 8; ks++) wgmma_n32<1, 0>(d, da + ks * 128, db + (ks >> 2) * 256 + (ks & 3) * 2, 1);
        wg_commit();
        wg_wait<0>();
        if (c.lead) mbar_arrive(sb + wk::UE + u * 8);
        __syncwarp();
        c.us += 2;
        if (c.us == 10) { c.us = 0; c.uph ^= 1; }
      }
      if (mb == mb0 + nh - 1) {
        for (int a = 0; a < 7; a++) c.a_rel(a);
        for (int a = 0; a < 3; a++) c.b_rel(a);
        __syncwarp();
      }
      acc_fence(d);
      const uint32_t st = sb + wk::ST, xch = st + 8192 + (threadIdx.x & 127) * 16;
      if (c.lead) bulk_wait_read0();
      if (c.wg == 1) {
        bar_sync(2, 128);
#pragma unroll
        for (int i = 0; i < 4; i++) sts128f(xch + i * 2048, *(const float(*)[4])&d[4 * i]);
        bar_sync(3, 256);
        bar_sync(4, 256);
      } else {
        const int l7 = c.lane & 7, li = c.lane >> 3;
        bar_sync(3, 256);
#pragma unroll
        for (int i = 0; i < 4; i++) {
          const float4 v = lds128f(xch + i * 2048);
          d[4 * i] += v.x; d[4 * i + 1] += v.y; d[4 * i + 2] += v.z; d[4 * i + 3] += v.w;
        }
        bar_arrive(4, 256);
#pragma unroll
        for (int i = 0; i < 4; i += 2)
          stsm4t(st + (8 * (i + (li >> 1)) + l7) * 128 + (((2 * c.wq + (li & 1)) ^ l7) << 4), pack2(d[4 * i], d[4 * i + 1]),
                 pack2(d[4 * i + 2], d[4 * i + 3]), pack2(d[4 * i + 4], d[4 * i + 5]), pack2(d[4 * i + 6], d[4 * i + 7]));
        fence_proxy_async_smem();
        bar_sync(1, 128);
        if (c.lead) { tma2d_store(&tm->o32, 64 * mb, SEG * seg, st); bulk_commit(); }
        __syncwarp();
      }
      }
    }
  }
  if (c.lead) bulk_wait0();
}

__device__ __forceinline__ void work_signaller(uint32_t sb) {
  int budget = 1 << 20;
  uint32_t ph = 0;
  for (uint32_t n = 0;; n++) {
    mbar_wait(sb + wk::IF + (n & 1) * 8, (n >> 1) & 1, budget);
    const int it = __reduce_max_sync(0xffffffffu, budget > 0 ? (int)lds32(sb + wk::ITEM + (n & 1) * 4) : wk::NITEM);
    if (elect()) mbar_arrive(sb + wk::IE + (n & 1) * 8);
    int type, tile, sub, nh;
    item_decode(it, type, tile, sub, nh);
    if (type == wk::END) break;
    if (type == wk::PA)
      for (int i = 0; i < 4 * nh; i++) {
        mbar_wait(sb + wk::PS + (i & 3) * 8, ph, budget);
        if ((i & 3) == 3) ph ^= 1;
        if (elect()) red_release(&g_fl.p[4 * tile + (i & 3)], 2);
      }
  }
}

__global__ void __launch_bounds__(384, 1) k_work(const __grid_constant__ WorkMaps tm) {
  extern __shared__ __align__(1024) uint8_t smem[];
  const uint32_t sb = smem_u32(smem);
  if (threadIdx.x == 0) {
    for (int i = 0; i < 7; i++) { mbar_init(sb + wk::AF + i * 8, 1); mbar_init(sb + wk::AE + i * 8, 2); }
    for (int i = 0; i < 3; i++) { mbar_init(sb + wk::BF + i * 8, 1); mbar_init(sb + wk::BE + i * 8, 2); }
    for (int i = 0; i < 4; i++) { mbar_init(sb + wk::MF + i * 8, 1); mbar_init(sb + wk::PS + i * 8, 2); }
    for (int i = 0; i < 10; i++) { mbar_init(sb + wk::UF + i * 8, 1); mbar_init(sb + wk::UE + i * 8, 1); }
    for (int i = 0; i < 2; i++) { mbar_init(sb + wk::IF + i * 8, 1); mbar_init(sb + wk::IE + i * 8, 9); }
    asm volatile("fence.mbarrier_init.release.cluster;" ::: "memory");
  }
  __syncthreads();
  if (__reduce_max_sync(0xffffffffu, threadIdx.x >> 7) < 2) {
    reg_inc<232>();
    work_consumer(sb, &tm);
    pdl_wait();
  } else {
    reg_dec<40>();
    const int w = __reduce_max_sync(0xffffffffu, threadIdx.x >> 5);
    if (w == 8) work_producer(sb, &tm);
    else if (w == 9) work_signaller(sb);
  }
}
#define R0 224
#define R1 208
#define RAUX 72
#define U0 3
#define U1 3
__global__ void __launch_bounds__(384, 1) k_chain(const bf16* __restrict__ mem0, int ncl, const __grid_constant__ Maps tm) {
  extern __shared__ __align__(1024) uint8_t smem[];
  const uint32_t sb = smem_u32(smem);
  int c, j;
  asm("mov.u32 %0, %%clusterid.x;" : "=r"(c));
  asm("mov.u32 %0, %%cluster_ctarank;" : "=r"(j));
  const int w = __reduce_max_sync(0xffffffffu, threadIdx.x >> 5), lane = threadIdx.x & 31;
  uint32_t side = 0, both = 1, rank = 0;
  const bool leader = j == 0 && threadIdx.x == 32;
  if (leader) { side = ld_relaxed(&g_side[smid()]) & 1; rank = atomicAdd(&g_fl.side[side], 1); }
  if (threadIdx.x == 64) { prefetch_map(&tm.a64); prefetch_map(&tm.v64); prefetch_map(&tm.x64); prefetch_map(&tm.x32); prefetch_map(&tm.u32); prefetch_map(&tm.u64); }
  chain_init(sb);
  helper_init(sb);
  __syncthreads();
  asm volatile("barrier.cluster.arrive.relaxed.aligned;" ::: "memory");
  uint32_t role = 0;
  if (leader) {
    uint32_t n0, n1;
    int budget = 1 << 16;
    do { n0 = ld_relaxed(&g_fl.side[0]); n1 = ld_relaxed(&g_fl.side[1]); } while (n0 + n1 < (uint32_t)ncl && --budget > 0);
    const uint32_t big = n1 > n0, nb = big ? n1 : n0;
    role = (side == big ? rank : nb + rank) | (side << 8) | ((nb < NCH) << 9);
  }
  __syncwarp();
  asm volatile("barrier.cluster.wait.aligned;" ::: "memory");
  if (leader)
    for (int k = 0; k < CL; k++) stasync32(mapa(sb + ch::FLAG + 4, k), role, mapa(sb + ch::B_ROLE, k));
  __syncwarp();
  {
    int budget = 1 << 18;
    mbar_wait(sb + ch::B_ROLE, 0, budget);
    role = __reduce_max_sync(0xffffffffu, lds32(sb + ch::FLAG + 4));
    c = role & 255; side = (role >> 8) & 1; both = role >> 9;
  }
  if (threadIdx.x == 0) g_side[smid()] = 2;
  if (c >= NCH + NHELP) { pdl_wait(); pdl_launch(); return; }
  pdl_wait();
  const uint32_t zero = (uint32_t)((uint64_t)mem0 >> 60);
  if (NHELP == 0 || c < NCH) {
    if (w < 4) {
      reg_inc<R0>();
      chain_main_role<0, U0>(sb, c, j, w, lane, zero, side, both, &tm);
      cluster_sync_all();
    } else if (w < 8) {
      reg_inc<R1>();
      chain_main_role<1, U1>(sb, c, j, w - 4, lane, zero, side, both, &tm);
      cluster_sync_all();
    } else {
      reg_dec<RAUX>();
      chain_aux_role(sb, c, j, w - 8, lane, zero, side, mem0, &tm);
      cluster_sync_all();
    }
  } else {
    const int nhelp = min(ncl - NCH, NHELP);
    if (w < 8) {
      reg_inc<216>();
      for (int g = c - NCH; g < NHELP; g += nhelp) {
        if (g < 4) helper_consumer<3>(sb, w >> 2, 3 * g, j, &tm); else helper_consumer<2>(sb, w >> 2, 2 * g + 4, j, &tm);
        cluster_sync_all();
        if (g + nhelp < NHELP) { helper_init(sb, true); cluster_sync_all(); }
      }
    } else {
      reg_dec<72>();
      for (int g = c - NCH; g < NHELP; g += nhelp) {
        if (w == 8) helper_producer(sb, g < 4 ? 3 * g : 2 * g + 4, g < 4 ? 3 : 2, j, &tm);
        cluster_sync_all();
        if (g + nhelp < NHELP) cluster_sync_all();
      }
    }
  }
}

#define L2PROMO CU_TENSOR_MAP_L2_PROMOTION_L2_128B
typedef CUresult (*EncodeFn)(CUtensorMap*, CUtensorMapDataType, cuuint32_t, void*, const cuuint64_t*, const cuuint64_t*, const cuuint32_t*,
                             const cuuint32_t*, CUtensorMapInterleave, CUtensorMapSwizzle, CUtensorMapL2promotion, CUtensorMapFloatOOBfill);
static void make_map(EncodeFn enc, CUtensorMap* m, const void* p, uint64_t cols, uint64_t rows, uint32_t boxRows, uint32_t boxCols = 64) {
  const cuuint64_t gd[2] = {cols, rows}, gs[1] = {cols * 2};
  const cuuint32_t bx[2] = {boxCols, boxRows}, es[2] = {1, 1};
  enc(m, CU_TENSOR_MAP_DATA_TYPE_BFLOAT16, 2, (void*)p, gd, gs, bx, es, CU_TENSOR_MAP_INTERLEAVE_NONE,
      boxCols == 64 ? CU_TENSOR_MAP_SWIZZLE_128B : CU_TENSOR_MAP_SWIZZLE_NONE,
      L2PROMO, CU_TENSOR_MAP_FLOAT_OOB_FILL_NONE);
}

static void make_map3(EncodeFn enc, CUtensorMap* m, const void* p, uint64_t cols, uint64_t rows, uint32_t boxRows, uint32_t boxBlocks) {
  const cuuint64_t gd[3] = {64, rows, cols / 64}, gs[2] = {cols * 2, 128};
  const cuuint32_t bx[3] = {64, boxRows, boxBlocks}, es[3] = {1, 1, 1};
  enc(m, CU_TENSOR_MAP_DATA_TYPE_BFLOAT16, 3, (void*)p, gd, gs, bx, es, CU_TENSOR_MAP_INTERLEAVE_NONE, CU_TENSOR_MAP_SWIZZLE_128B,
      L2PROMO, CU_TENSOR_MAP_FLOAT_OOB_FILL_NONE);
}

extern "C" void kernel_launch(void* const* d_in, const int* in_sizes, int n_in, void* d_out, int out_size) {
  const bf16* x = (const bf16*)d_in[0];
  const bf16* mem0 = (const bf16*)d_in[1];
  const bf16* gw = (const bf16*)d_in[10];
  void* fn = nullptr;
  cudaDriverEntryPointQueryResult qr;
  cudaGetDriverEntryPoint("cuTensorMapEncodeTiled", &fn, cudaEnableDefault, &qr);
  EncodeFn enc = (EncodeFn)fn;
  void *pA, *pV, *pU, *pP, *pM;
  cudaGetSymbolAddress(&pA, g_At); cudaGetSymbolAddress(&pV, g_VOt); cudaGetSymbolAddress(&pU, g_U);
  cudaGetSymbolAddress(&pP, g_P); cudaGetSymbolAddress(&pM, g_mem);
  PrepMaps pm;
  Maps tm;
  WorkMaps wm;
  make_map(enc, &tm.x32, x, D, NTOK, 32); make_map(enc, &tm.x64, x, D, NTOK, 64);
  make_map(enc, &tm.u16, pU, D, NSEG * UROWS, 16); make_map(enc, &tm.u32, pU, D, NSEG * UROWS, 32); make_map(enc, &tm.u64, pU, D, NSEG * UROWS, 64);
  make_map(enc, &tm.m8, pM, D, NSEG * MT, 8);
  make_map(enc, &tm.a64, pA, D, NH * D, 64); make_map(enc, &tm.v64, pV, D, NH * D, 64);
  make_map3(enc, &pm.wq152, d_in[2], 4096, D, 152, 4); make_map3(enc, &pm.wq144, d_in[2], 4096, D, 144, 4);
  make_map3(enc, &pm.wv152, d_in[4], 4096, D, 152, 4); make_map3(enc, &pm.wv144, d_in[4], 4096, D, 144, 4);
  make_map3(enc, &pm.wk3, d_in[3], 4096, D, 64, 4); make_map(enc, &pm.wo256, d_in[5], D, 4096, 256);
  make_map(enc, &pm.a152, pA, D, NH * D, 64, 152); make_map(enc, &pm.a144, pA, D, NH * D, 64, 144);
  make_map(enc, &pm.v152, pV, D, NH * D, 64, 152); make_map(enc, &pm.v144, pV, D, NH * D, 64, 144);
  make_map(enc, &wm.x128, x, D, NTOK, 128); make_map(enc, &wm.u128, pU, D, NSEG * UROWS, 128);
  make_map(enc, &wm.a256, pA, D, NH * D, 256); make_map(enc, &wm.a192, pA, D, NH * D, 192);
  make_map3(enc, &wm.w1a, d_in[8], DFF, D, 64, 4); make_map3(enc, &wm.w1b, d_in[8], DFF, D, 64, 3);
  make_map3(enc, &wm.w2b, d_in[9], D, DFF, 64, 2); make_map(enc, &wm.w2c, d_in[9], D, DFF, 256); make_map(enc, &wm.w2d, d_in[9], D, DFF, 192);
  make_map3(enc, &wm.p3, pP, UROWS, NTOK, SEG, 4); make_map3(enc, &wm.m3, pM, D, NSEG * MT, MT, 7);
  make_map(enc, &wm.o32, d_out, D, NTOK, 32);
  wm.u32 = tm.u32;
  const int sm1 = ch::SIZE > hp::SIZE ? ch::SIZE : hp::SIZE;
  cudaFuncSetAttribute(k_prep, cudaFuncAttributeMaxDynamicSharedMemorySize, pr::SIZE);
  cudaFuncSetAttribute(k_chain, cudaFuncAttributeMaxDynamicSharedMemorySize, sm1);
  cudaFuncSetAttribute(k_work, cudaFuncAttributeMaxDynamicSharedMemorySize, wk::SIZE);
  cudaStream_t st = cudaStreamPerThread;
  k_prep<<<132, 384, pr::SIZE, st>>>(x, gw, pm);
  cudaLaunchConfig_t cfg = {};
  cudaLaunchAttribute at[2];
  at[0].id = cudaLaunchAttributeProgrammaticStreamSerialization;
  at[0].val.programmaticStreamSerializationAllowed = 1;
  at[1].id = cudaLaunchAttributeClusterDimension;
  at[1].val.clusterDim.x = CL; at[1].val.clusterDim.y = 1; at[1].val.clusterDim.z = 1;
  cfg.stream = st; cfg.attrs = at; cfg.blockDim = dim3(384);
  cfg.gridDim = dim3((NCH + NHELP) * CL); cfg.dynamicSmemBytes = sm1; cfg.numAttrs = 2;
  int ncl = NCH + NHELP;
  cudaOccupancyMaxActiveClusters(&ncl, k_chain, &cfg);
  ncl = ncl <= NCH ? NCH + 1 : ncl > 16 ? 16 : ncl;
  cfg.gridDim = dim3(ncl * CL);
  cudaLaunchKernelEx(&cfg, k_chain, mem0, ncl, tm);
  cfg.gridDim = dim3(NWORK); cfg.dynamicSmemBytes = wk::SIZE; cfg.numAttrs = 1;
  cudaLaunchKernelEx(&cfg, k_work, wm);
}
```
